```python
import torch

def _softmax(x, axis=-1):
    return torch.softmax(x, dim=axis)
def _gelu(x):
    return torch.nn.functional.gelu(x, approximate="tanh")
def _silu(x):
    return torch.nn.functional.silu(x)
def _sigmoid(x):
    return torch.sigmoid(x)
def _layernorm(x, axis=-1, eps=1e-5):
    m = x.mean(dim=axis, keepdim=True)
    v = x.var(dim=axis, keepdim=True, unbiased=False)
    return (x - m) / torch.sqrt(v + eps)
def _scatter_add(tgt, idx, src, axis=0):
    return tgt.clone().index_add_(axis, idx, src)
def _segment_sum(src, seg, n):
    out = torch.zeros((n,) + src.shape[1:], dtype=src.dtype)
    return out.index_add_(0, seg, src)
def _pad(x, pw):
    flat = tuple(v for pair in reversed(pw) for v in pair)
    return torch.nn.functional.pad(x, flat)

kernel_name = 'recurrent_scan__spectral_gfnet__dense_activation_gelu__prompt'

def setup_inputs():

    _w = (lambda a: (lambda t: t.to(torch.bfloat16) if t.is_floating_point() else t)(torch.as_tensor(a)))
    def _A_setup():
        B, S, D = 1, 2048, 512
        Df = D // 2 + 1
        return {
            "x": _w((lambda *s: torch.randn(*s, dtype=torch.bfloat16) * 0.05)(B, S, D)),
            "w_r": _w((lambda *s: torch.randn(*s, dtype=torch.bfloat16) * 3.2)(S, Df) * 0.02),
            "w_i": _w((lambda *s: torch.randn(*s, dtype=torch.bfloat16) * 3.2)(S, Df) * 0.02),
        }
    _A_in = _A_setup()

    def _B_setup():
        B, S, D, F = 1, 2048, 512, 1792
        return {
            "x": _w((lambda *s: torch.randn(*s, dtype=torch.bfloat16) * 0.05)(B, S, D)),
            "w1": _w((lambda *s: torch.randn(*s, dtype=torch.bfloat16) * 3.2)(D, F) * (D ** -0.5)),
            "b1": _w((lambda *s: torch.randn(*s, dtype=torch.bfloat16) * 3.2)(F) * 0.01),
            "w2": _w((lambda *s: torch.randn(*s, dtype=torch.bfloat16) * 0.4)(F, D) * (F ** -0.5)),
            "b2": _w((lambda *s: torch.randn(*s, dtype=torch.bfloat16) * 0.4)(D) * 0.01),
        }
    _B_in = _B_setup()

    return {
        "A_x": _A_in["x"],
        "A_w_r": _A_in["w_r"],
        "A_w_i": _A_in["w_i"],
        "B_x": _B_in["x"],
        "B_w1": _B_in["w1"],
        "B_b1": _B_in["b1"],
        "B_w2": _B_in["w2"],
        "B_b2": _B_in["b2"],
    }

def reference(A_x, A_w_r, A_w_i, B_x, B_w1, B_b1, B_w2, B_b2):
    def _A_ref(x, w_r, w_i):
        B, S, D = x.shape
        X = (lambda x, axes=(-2,-1): torch.fft.rfft2(x.float(), dim=axes))(x, axes=(-2, -1))
        W = w_r + 1j * w_i
        X = X * W
        y = (lambda x, s, axes=(-2,-1): torch.fft.irfft2(x, s=s, dim=axes).to(torch.bfloat16))(X, (S, D), axes=(-2, -1))
        return y

    def _B_ref(x, w1, b1, w2, b2):
        h = torch.einsum("bsd,df->bsf", x, w1) + b1
        h = _gelu(h)
        return torch.einsum("bsf,fd->bsd", h, w2) + b2

    x = A_x
    xn = _layernorm(x, axis=-1)
    s = _A_ref(xn, A_w_r, A_w_i)
    g = _silu(_B_ref(xn, B_w1, B_b1, B_w2, B_b2))
    return x + s * g
```

```cpp
#include <cuda_runtime.h>
#include <cuda_bf16.h>
#include <cuda.h>
#include <stdint.h>

namespace {

constexpr int S_ = 2048, D_ = 512, F_ = 1792, DF_ = 257;
constexpr int FC = 224;
constexpr int NSPLIT = 8;
constexpr int NJOB = 4;

__device__ float2 g_spec[256 * 2048];
__device__ uint4 g_part[16 * NJOB * 8 * 8 * 256];

__device__ __forceinline__ uint32_t smem_u32(const void* p) { return (uint32_t)__cvta_generic_to_shared(p); }
__device__ __forceinline__ float bf16r(float x) { return __bfloat162float(__float2bfloat16_rn(x)); }
__device__ __forceinline__ float bflo(uint32_t w) { return __uint_as_float(w << 16); }
__device__ __forceinline__ float bfhi(uint32_t w) { return __uint_as_float(w & 0xffff0000u); }
__device__ __forceinline__ uint32_t pack_bf16(float lo, float hi) {
  uint32_t r;
  asm("cvt.rn.bf16x2.f32 %0, %1, %2;" : "=r"(r) : "f"(hi), "f"(lo));
  return r;
}
__device__ __forceinline__ void named_bar(int id, int n) { asm volatile("bar.sync %0, %1;" ::"r"(id), "r"(n) : "memory"); }

__device__ __forceinline__ void mbar_init(uint32_t bar, int cnt) { asm volatile("mbarrier.init.shared::cta.b64 [%0], %1;" ::"r"(bar), "r"(cnt) : "memory"); }
__device__ __forceinline__ void mbar_expect_tx(uint32_t bar, uint32_t bytes) { asm volatile("mbarrier.arrive.expect_tx.shared::cta.b64 _, [%0], %1;" ::"r"(bar), "r"(bytes) : "memory"); }
__device__ __forceinline__ void mbar_arrive(uint32_t bar) { asm volatile("mbarrier.arrive.shared::cta.b64 _, [%0];" ::"r"(bar) : "memory"); }
__device__ __forceinline__ bool mbar_try(uint32_t bar, uint32_t parity) {
  uint32_t ok;
  asm volatile("{\n.reg .pred p;\nmbarrier.try_wait.parity.shared::cta.b64 p, [%1], %2;\nselp.u32 %0, 1, 0, p;\n}\n" : "=r"(ok) : "r"(bar), "r"(parity) : "memory");
  return ok != 0;
}
__device__ __forceinline__ void mbar_wait(uint32_t bar, uint32_t parity) {
  int it = 0;
  while (!mbar_try(bar, parity)) {
    if (++it > (1 << 22)) __trap();
  }
}
__device__ __forceinline__ void tma_load_3d(uint32_t dst, const CUtensorMap* map, int c0, int c1, int c2, uint32_t bar) {
  asm volatile("cp.async.bulk.tensor.3d.shared::cluster.global.mbarrier::complete_tx::bytes [%0], [%1, {%3, %4, %5}], [%2];"
               ::"r"(dst), "l"((uint64_t)map), "r"(bar), "r"(c0), "r"(c1), "r"(c2) : "memory");
}
__device__ __forceinline__ void wgmma_fence() { asm volatile("wgmma.fence.sync.aligned;" ::: "memory"); }
__device__ __forceinline__ void wgmma_commit() { asm volatile("wgmma.commit_group.sync.aligned;" ::: "memory"); }
template <int N> __device__ __forceinline__ void wgmma_wait() { asm volatile("wgmma.wait_group.sync.aligned %0;" ::"n"(N) : "memory"); }
__device__ __forceinline__ uint64_t make_desc(uint32_t addr, uint32_t lbo_bytes, uint32_t sbo_bytes, uint32_t swz) {
  uint64_t d = 0;
  d |= (uint64_t)((addr & 0x3FFFF) >> 4);
  d |= (uint64_t)((lbo_bytes & 0x3FFFF) >> 4) << 16;
  d |= (uint64_t)((sbo_bytes & 0x3FFFF) >> 4) << 32;
  d |= (uint64_t)swz << 62;
  return d;
}

__device__ __forceinline__ void wgmma_n224_ss(float (&d)[112], uint64_t da, uint64_t db, int scale_d) {
  asm volatile("{\n.reg .pred p;\nsetp.ne.b32 p, %114, 0;\n"
    "wgmma.mma_async.sync.aligned.m64n224k16.f32.bf16.bf16 {%0, %1, %2, %3, %4, %5, %6, %7, %8, %9, %10, %11, %12, %13, %14, %15, %16, %17, %18, %19, %20, %21, %22, %23, %24, %25, %26, %27, %28, %29, %30, %31, %32, %33, %34, %35, %36, %37, %38, %39, %40, %41, %42, %43, %44, %45, %46, %47, %48, %49, %50, %51, %52, %53, %54, %55, %56, %57, %58, %59, %60, %61, %62, %63, %64, %65, %66, %67, %68, %69, %70, %71, %72, %73, %74, %75, %76, %77, %78, %79, %80, %81, %82, %83, %84, %85, %86, %87, %88, %89, %90, %91, %92, %93, %94, %95, %96, %97, %98, %99, %100, %101, %102, %103, %104, %105, %106, %107, %108, %109, %110, %111}, %112, %113, p, 1, 1, 0, 1;\n}\n"
    : "+f"(d[0]), "+f"(d[1]), "+f"(d[2]), "+f"(d[3]), "+f"(d[4]), "+f"(d[5]), "+f"(d[6]), "+f"(d[7]), "+f"(d[8]), "+f"(d[9]), "+f"(d[10]), "+f"(d[11]), "+f"(d[12]), "+f"(d[13]), "+f"(d[14]), "+f"(d[15]), "+f"(d[16]), "+f"(d[17]), "+f"(d[18]), "+f"(d[19]), "+f"(d[20]), "+f"(d[21]), "+f"(d[22]), "+f"(d[23]), "+f"(d[24]), "+f"(d[25]), "+f"(d[26]), "+f"(d[27]), "+f"(d[28]), "+f"(d[29]), "+f"(d[30]), "+f"(d[31]), "+f"(d[32]), "+f"(d[33]), "+f"(d[34]), "+f"(d[35]), "+f"(d[36]), "+f"(d[37]), "+f"(d[38]), "+f"(d[39]), "+f"(d[40]), "+f"(d[41]), "+f"(d[42]), "+f"(d[43]), "+f"(d[44]), "+f"(d[45]), "+f"(d[46]), "+f"(d[47]), "+f"(d[48]), "+f"(d[49]), "+f"(d[50]), "+f"(d[51]), "+f"(d[52]), "+f"(d[53]), "+f"(d[54]), "+f"(d[55]), "+f"(d[56]), "+f"(d[57]), "+f"(d[58]), "+f"(d[59]), "+f"(d[60]), "+f"(d[61]), "+f"(d[62]), "+f"(d[63]), "+f"(d[64]), "+f"(d[65]), "+f"(d[66]), "+f"(d[67]), "+f"(d[68]), "+f"(d[69]), "+f"(d[70]), "+f"(d[71]), "+f"(d[72]), "+f"(d[73]), "+f"(d[74]), "+f"(d[75]), "+f"(d[76]), "+f"(d[77]), "+f"(d[78]), "+f"(d[79]), "+f"(d[80]), "+f"(d[81]), "+f"(d[82]), "+f"(d[83]), "+f"(d[84]), "+f"(d[85]), "+f"(d[86]), "+f"(d[87]), "+f"(d[88]), "+f"(d[89]), "+f"(d[90]), "+f"(d[91]), "+f"(d[92]), "+f"(d[93]), "+f"(d[94]), "+f"(d[95]), "+f"(d[96]), "+f"(d[97]), "+f"(d[98]), "+f"(d[99]), "+f"(d[100]), "+f"(d[101]), "+f"(d[102]), "+f"(d[103]), "+f"(d[104]), "+f"(d[105]), "+f"(d[106]), "+f"(d[107]), "+f"(d[108]), "+f"(d[109]), "+f"(d[110]), "+f"(d[111])
    : "l"(da), "l"(db), "r"(scale_d));
}
__device__ __forceinline__ void wgmma_n128_rs(float (&d)[64], uint32_t a0, uint32_t a1, uint32_t a2, uint32_t a3, uint64_t db, int scale_d) {
  asm volatile("{\n.reg .pred p;\nsetp.ne.b32 p, %69, 0;\n"
    "wgmma.mma_async.sync.aligned.m64n128k16.f32.bf16.bf16 {%0, %1, %2, %3, %4, %5, %6, %7, %8, %9, %10, %11, %12, %13, %14, %15, %16, %17, %18, %19, %20, %21, %22, %23, %24, %25, %26, %27, %28, %29, %30, %31, %32, %33, %34, %35, %36, %37, %38, %39, %40, %41, %42, %43, %44, %45, %46, %47, %48, %49, %50, %51, %52, %53, %54, %55, %56, %57, %58, %59, %60, %61, %62, %63}, {%64, %65, %66, %67}, %68, p, 1, 1, 1;\n}\n"
    : "+f"(d[0]), "+f"(d[1]), "+f"(d[2]), "+f"(d[3]), "+f"(d[4]), "+f"(d[5]), "+f"(d[6]), "+f"(d[7]), "+f"(d[8]), "+f"(d[9]), "+f"(d[10]), "+f"(d[11]), "+f"(d[12]), "+f"(d[13]), "+f"(d[14]), "+f"(d[15]), "+f"(d[16]), "+f"(d[17]), "+f"(d[18]), "+f"(d[19]), "+f"(d[20]), "+f"(d[21]), "+f"(d[22]), "+f"(d[23]), "+f"(d[24]), "+f"(d[25]), "+f"(d[26]), "+f"(d[27]), "+f"(d[28]), "+f"(d[29]), "+f"(d[30]), "+f"(d[31]), "+f"(d[32]), "+f"(d[33]), "+f"(d[34]), "+f"(d[35]), "+f"(d[36]), "+f"(d[37]), "+f"(d[38]), "+f"(d[39]), "+f"(d[40]), "+f"(d[41]), "+f"(d[42]), "+f"(d[43]), "+f"(d[44]), "+f"(d[45]), "+f"(d[46]), "+f"(d[47]), "+f"(d[48]), "+f"(d[49]), "+f"(d[50]), "+f"(d[51]), "+f"(d[52]), "+f"(d[53]), "+f"(d[54]), "+f"(d[55]), "+f"(d[56]), "+f"(d[57]), "+f"(d[58]), "+f"(d[59]), "+f"(d[60]), "+f"(d[61]), "+f"(d[62]), "+f"(d[63])
    : "r"(a0), "r"(a1), "r"(a2), "r"(a3), "l"(db), "r"(scale_d));
}


__device__ __forceinline__ float2 cadd(float2 a, float2 b) { return make_float2(a.x + b.x, a.y + b.y); }
__device__ __forceinline__ float2 csub(float2 a, float2 b) { return make_float2(a.x - b.x, a.y - b.y); }
__device__ __forceinline__ float2 cmul(float2 a, float2 b) { return make_float2(a.x * b.x - a.y * b.y, a.x * b.y + a.y * b.x); }
__device__ __forceinline__ float2 cconj(float2 a) { return make_float2(a.x, -a.y); }

template <int DIR> __device__ __forceinline__ void dft4(float2& a0, float2& a1, float2& a2, float2& a3) {
  float2 t0 = cadd(a0, a2), t1 = csub(a0, a2), t2 = cadd(a1, a3), t3 = csub(a1, a3);
  float2 t3r = DIR < 0 ? make_float2(t3.y, -t3.x) : make_float2(-t3.y, t3.x);
  a0 = cadd(t0, t2); a2 = csub(t0, t2); a1 = cadd(t1, t3r); a3 = csub(t1, t3r);
}
template <int DIR> __device__ __forceinline__ float2 mulw(float2 v, float c, float s) {
  return DIR < 0 ? make_float2(v.x * c + v.y * s, v.y * c - v.x * s) : make_float2(v.x * c - v.y * s, v.y * c + v.x * s);
}
template <int DIR> __device__ __forceinline__ float2 muli(float2 v) {
  return DIR < 0 ? make_float2(v.y, -v.x) : make_float2(-v.y, v.x);
}
#define O16(k) (4 * ((k) & 3) + ((k) >> 2))
#define O8(k) (2 * ((k) & 3) + ((k) >> 2))
template <int DIR> __device__ __forceinline__ void dft16(float2 (&v)[16]) {
  constexpr float C1 = 0.92387953251128674f, S1 = 0.38268343236508977f, R = 0.70710678118654752f;
#pragma unroll
  for (int n2 = 0; n2 < 4; n2++) dft4<DIR>(v[n2], v[4 + n2], v[8 + n2], v[12 + n2]);
  v[5] = mulw<DIR>(v[5], C1, S1);
  v[6] = mulw<DIR>(v[6], R, R);
  v[7] = mulw<DIR>(v[7], S1, C1);
  v[9] = mulw<DIR>(v[9], R, R);
  v[10] = muli<DIR>(v[10]);
  v[11] = mulw<DIR>(v[11], -R, R);
  v[13] = mulw<DIR>(v[13], S1, C1);
  v[14] = mulw<DIR>(v[14], -R, R);
  v[15] = mulw<DIR>(v[15], -C1, -S1);
#pragma unroll
  for (int k1 = 0; k1 < 4; k1++) dft4<DIR>(v[4 * k1], v[4 * k1 + 1], v[4 * k1 + 2], v[4 * k1 + 3]);
}
template <int DIR> __device__ __forceinline__ void dft8(float2 (&v)[8]) {
  constexpr float R = 0.70710678118654752f;
  dft4<DIR>(v[0], v[2], v[4], v[6]);
  dft4<DIR>(v[1], v[3], v[5], v[7]);
  v[3] = mulw<DIR>(v[3], R, R);
  v[5] = muli<DIR>(v[5]);
  v[7] = mulw<DIR>(v[7], -R, R);
#pragma unroll
  for (int k1 = 0; k1 < 4; k1++) {
    float2 a = v[2 * k1], b = v[2 * k1 + 1];
    v[2 * k1] = cadd(a, b); v[2 * k1 + 1] = csub(a, b);
  }
}
template <int DIR, int N> __device__ __forceinline__ float2 twmul(float2 v, int m) {
  m &= (N - 1);
  if (m >= N / 2) m -= N;
  float s, c;
  __sincosf((float)m * (6.283185307179586f / N), &s, &c);
  return mulw<DIR>(v, c, s);
}

constexpr int ROWP = 274;
constexpr int FFTBUF = 8 * ROWP;

__device__ __forceinline__ void fft_phase1(const __nv_bfloat16* __restrict__ x, int s0, float2* buf, int t, int barid) {
  {
    const int r = t >> 4, n2 = t & 15;
    const uint32_t* xw = reinterpret_cast<const uint32_t*>(x + (size_t)(s0 + r) * D_);
    uint32_t w[16];
#pragma unroll
    for (int n1 = 0; n1 < 16; n1++) w[n1] = __ldg(xw + 16 * n1 + n2);
    float sum = 0.f;
#pragma unroll
    for (int n1 = 0; n1 < 16; n1++) sum += bflo(w[n1]) + bfhi(w[n1]);
#pragma unroll
    for (int o = 1; o < 16; o <<= 1) sum += __shfl_xor_sync(0xffffffffu, sum, o);
    const float mean = sum * (1.0f / D_);
    float sq = 0.f;
#pragma unroll
    for (int n1 = 0; n1 < 16; n1++) {
      float a = bflo(w[n1]) - mean, b = bfhi(w[n1]) - mean;
      sq += a * a + b * b;
    }
#pragma unroll
    for (int o = 1; o < 16; o <<= 1) sq += __shfl_xor_sync(0xffffffffu, sq, o);
    const float mb = bf16r(mean);
    const float den = bf16r(sqrtf(bf16r(bf16r(sq * (1.0f / D_)) + 1e-5f)));
    float2 v[16];
#pragma unroll
    for (int n1 = 0; n1 < 16; n1++) {
      v[n1].x = bf16r(bf16r(bflo(w[n1]) - mb) / den);
      v[n1].y = bf16r(bf16r(bfhi(w[n1]) - mb) / den);
    }
    float2* rb = buf + r * ROWP;
    dft16<-1>(v);
#pragma unroll
    for (int k1 = 0; k1 < 16; k1++) {
      float2 u = v[O16(k1)];
      if (k1) u = twmul<-1, 256>(u, n2 * k1);
      rb[k1 * 17 + n2] = u;
    }
    __syncwarp();
    const int k1 = n2;
#pragma unroll
    for (int j = 0; j < 16; j++) v[j] = rb[k1 * 17 + j];
    __syncwarp();
    dft16<-1>(v);
#pragma unroll
    for (int k2 = 0; k2 < 16; k2++) rb[k1 + 16 * k2] = v[O16(k2)];
  }
  named_bar(barid, 128);
  {
    const int r = t & 7, jj = t >> 3;
    const float2* rb = buf + r * ROWP;
    float2* dst = g_spec + s0 + r;
#pragma unroll
    for (int i = 0; i < 8; i++) {
      const int j = jj + 16 * i;
      if (j == 0) {
        float2 z0 = rb[0], z128 = rb[128];
        dst[0] = make_float2(z0.x + z0.y, z0.x - z0.y);
        dst[(size_t)128 * S_] = cconj(z128);
      } else {
        float2 A = rb[j], B = cconj(rb[256 - j]);
        float2 E = make_float2(0.5f * (A.x + B.x), 0.5f * (A.y + B.y));
        float2 Dd = make_float2(0.5f * (A.x - B.x), 0.5f * (A.y - B.y));
        float2 O = make_float2(Dd.y, -Dd.x);
        float2 T = twmul<-1, 512>(O, j);
        dst[(size_t)j * S_] = cadd(E, T);
        dst[(size_t)(256 - j) * S_] = cconj(csub(E, T));
      }
    }
  }
  named_bar(barid, 128);
}

__device__ __forceinline__ void fft_phase2(int slot, const __nv_bfloat16* __restrict__ wr, const __nv_bfloat16* __restrict__ wi,
                                           float2* buf, int t, int barid) {
  float2* col = g_spec + (size_t)slot * S_;
  float2 v[16];
#pragma unroll
  for (int n1 = 0; n1 < 16; n1++) v[n1] = __ldcg(col + 128 * n1 + t);
  uint32_t wq[16];
#pragma unroll
  for (int i = 0; i < 16; i++) {
    const int u = t + 128 * i;
    uint32_t a = __ldg(reinterpret_cast<const unsigned short*>(wr) + (size_t)u * DF_ + slot);
    uint32_t b = __ldg(reinterpret_cast<const unsigned short*>(wi) + (size_t)u * DF_ + slot);
    wq[i] = a | (b << 16);
  }
  dft16<-1>(v);
#pragma unroll
  for (int k1 = 0; k1 < 16; k1++) {
    float2 u = v[O16(k1)];
    if (k1) u = twmul<-1, 2048>(u, t * k1);
    buf[k1 * 136 + t] = u;
  }
  named_bar(barid, 128);
  const int k1 = t >> 3, m2 = t & 7;
#pragma unroll
  for (int m1 = 0; m1 < 16; m1++) v[m1] = buf[k1 * 136 + 8 * m1 + m2];
  named_bar(barid, 128);
  dft16<-1>(v);
#pragma unroll
  for (int j1 = 0; j1 < 16; j1++) {
    float2 u = v[O16(j1)];
    if (j1) u = twmul<-1, 128>(u, m2 * j1);
    const int p = j1 * 16 + k1;
    buf[p * 8 + (m2 ^ ((p >> 1) & 7))] = u;
  }
  named_bar(barid, 128);
  float2 a[8], b[8];
  const int sw = (t >> 1) & 7;
#pragma unroll
  for (int m = 0; m < 8; m++) {
    a[m] = buf[t * 8 + (m ^ sw)];
    b[m] = buf[(t + 128) * 8 + (m ^ sw)];
  }
  named_bar(barid, 128);
  dft8<-1>(a);
  dft8<-1>(b);
  constexpr float SC = 1.0f / (2048.0f * 512.0f);
  float2 a2[8], b2[8];
  if (slot != 0) {
#pragma unroll
    for (int j2 = 0; j2 < 8; j2++) {
      a2[j2] = cmul(a[O8(j2)], make_float2(bflo(wq[2 * j2]) * SC, bfhi(wq[2 * j2]) * SC));
      b2[j2] = cmul(b[O8(j2)], make_float2(bflo(wq[2 * j2 + 1]) * SC, bfhi(wq[2 * j2 + 1]) * SC));
    }
  } else {
#pragma unroll
    for (int j2 = 0; j2 < 8; j2++) {
      buf[t + 256 * j2] = a[O8(j2)];
      buf[t + 128 + 256 * j2] = b[O8(j2)];
    }
    named_bar(barid, 128);
    const unsigned short* wru = reinterpret_cast<const unsigned short*>(wr);
    const unsigned short* wiu = reinterpret_cast<const unsigned short*>(wi);
#pragma unroll
    for (int i = 0; i < 16; i++) {
      const int u = t + 128 * i;
      const int um = (2048 - u) & 2047;
      float2 zm = cconj(buf[um]);
      float2 z = (i & 1) ? b[O8(i >> 1)] : a[O8(i >> 1)];
      float w0r = bflo(wq[i]), w0i = bfhi(wq[i]);
      float w0mr = bflo(__ldg(wru + (size_t)um * DF_)), w0mi = bflo(__ldg(wiu + (size_t)um * DF_));
      float w1r = bflo(__ldg(wru + (size_t)u * DF_ + 256)), w1i = bflo(__ldg(wiu + (size_t)u * DF_ + 256));
      float w1mr = bflo(__ldg(wru + (size_t)um * DF_ + 256)), w1mi = bflo(__ldg(wiu + (size_t)um * DF_ + 256));
      float2 h0 = make_float2(0.5f * (w0r + w0mr), 0.5f * (w0i - w0mi));
      float2 h1 = make_float2(0.5f * (w1r + w1mr), 0.5f * (w1i - w1mi));
      float2 P = make_float2(0.5f * SC * (h0.x + h1.x), 0.5f * SC * (h0.y + h1.y));
      float2 Q = make_float2(0.5f * SC * (h0.x - h1.x), 0.5f * SC * (h0.y - h1.y));
      float2 res = cadd(cmul(P, z), cmul(Q, zm));
      if (i & 1) b2[i >> 1] = res; else a2[i >> 1] = res;
    }
    named_bar(barid, 128);
  }
  dft8<1>(a2);
  dft8<1>(b2);
  {
    const int j1a = t >> 4, j1b = (t >> 4) + 8;
#pragma unroll
    for (int m = 0; m < 8; m++) {
      float2 ua = a2[O8(m)], ub = b2[O8(m)];
      if (m) { ua = twmul<1, 128>(ua, m * j1a); ub = twmul<1, 128>(ub, m * j1b); }
      buf[t * 8 + (m ^ sw)] = ua;
      buf[(t + 128) * 8 + (m ^ sw)] = ub;
    }
  }
  named_bar(barid, 128);
#pragma unroll
  for (int j1 = 0; j1 < 16; j1++) {
    const int p = j1 * 16 + k1;
    v[j1] = buf[p * 8 + (m2 ^ ((p >> 1) & 7))];
  }
  named_bar(barid, 128);
  dft16<1>(v);
#pragma unroll
  for (int m1 = 0; m1 < 16; m1++) {
    float2 u = twmul<1, 2048>(v[O16(m1)], (8 * m1 + m2) * k1);
    buf[k1 * 136 + 8 * m1 + m2] = u;
  }
  named_bar(barid, 128);
#pragma unroll
  for (int kk = 0; kk < 16; kk++) v[kk] = buf[kk * 136 + t];
  named_bar(barid, 128);
  dft16<1>(v);
#pragma unroll
  for (int n1 = 0; n1 < 16; n1++) col[128 * n1 + t] = v[O16(n1)];
}

__device__ __forceinline__ void fft_phase3(int s0, float2* buf, int t, int barid) {
  {
    const int r = t & 7, jj = t >> 3;
    float2* rb = buf + r * ROWP;
    const float2* src = g_spec + s0 + r;
    float2 yk[8], ym[8];
#pragma unroll
    for (int i = 0; i < 8; i++) {
      const int j = jj + 16 * i;
      yk[i] = __ldcg(src + (size_t)j * S_);
      ym[i] = __ldcg(src + (size_t)(j == 0 ? 128 : 256 - j) * S_);
    }
#pragma unroll
    for (int i = 0; i < 8; i++) {
      const int j = jj + 16 * i;
      if (j == 0) {
        rb[0] = make_float2(yk[i].x + yk[i].y, yk[i].x - yk[i].y);
        rb[128] = make_float2(2.f * ym[i].x, -2.f * ym[i].y);
      } else {
        float2 c = cconj(ym[i]);
        float2 Sx = cadd(yk[i], c), Dx = csub(yk[i], c);
        float2 T = twmul<1, 512>(Dx, j);
        float2 iT = make_float2(-T.y, T.x);
        rb[j] = cadd(Sx, iT);
        rb[256 - j] = cconj(csub(Sx, iT));
      }
    }
  }
  named_bar(barid, 128);
  {
    const int r = t >> 4, b = t & 15;
    float2* rb = buf + r * ROWP;
    float2 v[16];
#pragma unroll
    for (int a = 0; a < 16; a++) v[a] = rb[16 * a + b];
    __syncwarp();
    dft16<1>(v);
#pragma unroll
    for (int n1 = 0; n1 < 16; n1++) {
      float2 u = v[O16(n1)];
      if (n1) u = twmul<1, 256>(u, b * n1);
      rb[n1 * 17 + b] = u;
    }
    __syncwarp();
    const int n1 = b;
#pragma unroll
    for (int j = 0; j < 16; j++) v[j] = rb[n1 * 17 + j];
    __syncwarp();
    dft16<1>(v);
    uint32_t* sw = reinterpret_cast<uint32_t*>(rb);
#pragma unroll
    for (int n2 = 0; n2 < 16; n2++) sw[n1 + 16 * n2] = pack_bf16(v[O16(n2)].x, v[O16(n2)].y);
  }
}

__global__ void __launch_bounds__(256) k_phase1(const __nv_bfloat16* __restrict__ x) {
  __shared__ float2 buf[2 * FFTBUF];
  const int wg = threadIdx.x >> 7, t = threadIdx.x & 127;
  fft_phase1(x, blockIdx.x * 16 + wg * 8, buf + wg * FFTBUF, t, 1 + wg);
}
__global__ void __launch_bounds__(256) k_phase2(const __nv_bfloat16* __restrict__ wr, const __nv_bfloat16* __restrict__ wi) {
  __shared__ float2 buf[2 * FFTBUF];
  const int wg = threadIdx.x >> 7, t = threadIdx.x & 127;
  fft_phase2(blockIdx.x * 2 + wg, wr, wi, buf + wg * FFTBUF, t, 1 + wg);
}

constexpr int SM_X = 0;
constexpr int SM_RING = 131072;
constexpr int W1_STAGE = 14336;
constexpr int W2_HALF = 28672;
constexpr int SM_MISC = SM_RING + 4 * W1_STAGE;
constexpr int SM_B1 = SM_MISC;
constexpr int SM_BAR = SM_MISC + 512;
constexpr int SM_FFN_TOTAL = SM_BAR + 256;

__device__ __forceinline__ float gelu_tanh(float x) {
  float u = x * (0.7978845608028654f + 0.035677408136300125f * x * x);
  float th;
  asm("tanh.approx.f32 %0, %1;" : "=f"(th) : "f"(u));
  float hx = 0.5f * x;
  return fmaf(hx, th, hx);
}

__global__ void __launch_bounds__(288) k_ffn(const __nv_bfloat16* __restrict__ x, const __nv_bfloat16* __restrict__ b1,
                                             const __grid_constant__ CUtensorMap map_w1, const __grid_constant__ CUtensorMap map_w2) {
  extern __shared__ __align__(1024) uint8_t smem[];
  const uint32_t sb = smem_u32(smem);
  const int rt = blockIdx.x >> 3, sp = blockIdx.x & 7;
  const int warp = threadIdx.x >> 5, lane = threadIdx.x & 31;
  const uint32_t bar_full1 = sb + SM_BAR;
  const uint32_t bar_empty1 = sb + SM_BAR + 32;
  const uint32_t bar_full2 = sb + SM_BAR + 64;
  const uint32_t bar_xfree0 = sb + SM_BAR + 128;
  const uint32_t bar_g1done = sb + SM_BAR + 136;
  const uint32_t bar_j0done = sb + SM_BAR + 144;
  if (threadIdx.x == 0) {
    for (int i = 0; i < 4; i++) { mbar_init(bar_full1 + 8 * i, 1); mbar_init(bar_empty1 + 8 * i, 2); }
    for (int i = 0; i < 8; i++) mbar_init(bar_full2 + 8 * i, 1);
    mbar_init(bar_xfree0, 2); mbar_init(bar_g1done, 2); mbar_init(bar_j0done, 2);
    asm volatile("fence.mbarrier_init.release.cluster;" ::: "memory");
  }
  if (threadIdx.x < 112) reinterpret_cast<uint32_t*>(smem + SM_B1)[threadIdx.x] = __ldg(reinterpret_cast<const uint32_t*>(b1 + sp * FC) + threadIdx.x);
  __syncthreads();

  if (warp == 8) {
    if (lane == 0) {
      for (int ks = 0; ks < 16; ks++) {
        const int s = ks & 3;
        if (ks >= 4) mbar_wait(bar_empty1 + 8 * s, ((ks >> 2) - 1) & 1);
        mbar_expect_tx(bar_full1 + 8 * s, W1_STAGE);
        tma_load_3d(sb + SM_RING + s * W1_STAGE, &map_w1, 0, ks * 32, sp * 7, bar_full1 + 8 * s);
        if (ks == 11) {
          mbar_wait(bar_xfree0, 0);
          for (int h = 0; h < 2; h++) {
            mbar_expect_tx(bar_full2 + 8 * h, W2_HALF);
            tma_load_3d(sb + SM_X + h * W2_HALF, &map_w2, 0, sp * FC + h * 112, 0, bar_full2 + 8 * h);
          }
        }
      }
      mbar_wait(bar_g1done, 0);
      for (int h = 0; h < 2; h++) {
        mbar_expect_tx(bar_full2 + 8 * (2 + h), W2_HALF);
        tma_load_3d(sb + SM_X + 65536 + h * W2_HALF, &map_w2, 0, sp * FC + h * 112, 2, bar_full2 + 8 * (2 + h));
      }
      for (int h = 0; h < 2; h++) {
        mbar_expect_tx(bar_full2 + 8 * (4 + h), W2_HALF);
        tma_load_3d(sb + SM_RING + h * W2_HALF, &map_w2, 0, sp * FC + h * 112, 4, bar_full2 + 8 * (4 + h));
      }
      mbar_wait(bar_j0done, 0);
      for (int h = 0; h < 2; h++) {
        mbar_expect_tx(bar_full2 + 8 * (6 + h), W2_HALF);
        tma_load_3d(sb + SM_X + h * W2_HALF, &map_w2, 0, sp * FC + h * 112, 6, bar_full2 + 8 * (6 + h));
      }
    }
  } else {
    const int wg = warp >> 2, wq = warp & 3;
    {
      const int row0 = wg * 64 + wq * 16;
#pragma unroll 1
      for (int rr = 0; rr < 16; rr += 4) {
        uint4 va[4], vb[4];
#pragma unroll
        for (int i = 0; i < 4; i++) {
          const uint4* p = reinterpret_cast<const uint4*>(x + (size_t)(rt * 128 + row0 + rr + i) * D_);
          va[i] = __ldg(p + lane);
          vb[i] = __ldg(p + 32 + lane);
        }
#pragma unroll
        for (int i = 0; i < 4; i++) {
          uint32_t w[8] = {va[i].x, va[i].y, va[i].z, va[i].w, vb[i].x, vb[i].y, vb[i].z, vb[i].w};
          float sum = 0.f;
#pragma unroll
          for (int j = 0; j < 8; j++) sum += bflo(w[j]) + bfhi(w[j]);
#pragma unroll
          for (int o = 1; o < 32; o <<= 1) sum += __shfl_xor_sync(0xffffffffu, sum, o);
          const float mean = sum * (1.0f / D_);
          float sq = 0.f;
#pragma unroll
          for (int j = 0; j < 8; j++) {
            float a = bflo(w[j]) - mean, b = bfhi(w[j]) - mean;
            sq += a * a + b * b;
          }
#pragma unroll
          for (int o = 1; o < 32; o <<= 1) sq += __shfl_xor_sync(0xffffffffu, sq, o);
          const float mb = bf16r(mean);
          const float den = bf16r(sqrtf(bf16r(bf16r(sq * (1.0f / D_)) + 1e-5f)));
          uint32_t o[8];
#pragma unroll
          for (int j = 0; j < 8; j++) o[j] = pack_bf16(bf16r(bflo(w[j]) - mb) / den, bf16r(bfhi(w[j]) - mb) / den);
          const int row = row0 + rr + i;
          const uint32_t off = (uint32_t)row * 128 + (uint32_t)(((lane & 7) ^ (row & 7)) << 4);
          *reinterpret_cast<uint4*>(smem + SM_X + (lane >> 3) * 16384 + off) = make_uint4(o[0], o[1], o[2], o[3]);
          *reinterpret_cast<uint4*>(smem + SM_X + (4 + (lane >> 3)) * 16384 + off) = make_uint4(o[4], o[5], o[6], o[7]);
        }
      }
      asm volatile("fence.proxy.async.shared::cta;" ::: "memory");
      named_bar(1 + wg, 128);
    }
    const bool elect = (threadIdx.x & 127) == 0;
    uint32_t ha[56];
    {
      float acc[112];
#pragma unroll
      for (int i = 0; i < 112; i++) acc[i] = 0.f;
#pragma unroll 1
      for (int ks = 0; ks < 16; ks++) {
        const int s = ks & 3;
        mbar_wait(bar_full1 + 8 * s, (ks >> 2) & 1);
        wgmma_fence();
#pragma unroll
        for (int kk = 0; kk < 2; kk++) {
          const uint32_t aaddr = sb + SM_X + (ks >> 1) * 16384 + wg * 8192 + (ks & 1) * 64 + kk * 32;
          const uint32_t baddr = sb + SM_RING + s * W1_STAGE + kk * 1024;
          wgmma_n224_ss(acc, make_desc(aaddr, 16, 1024, 1), make_desc(baddr, 2048, 512, 2), 1);
        }
        wgmma_commit();
        if (ks > 0) {
          wgmma_wait<1>();
          if (elect) {
            mbar_arrive(bar_empty1 + 8 * ((ks - 1) & 3));
            if (ks == 8) mbar_arrive(bar_xfree0);
          }
        }
      }
      wgmma_wait<0>();
      if (elect) mbar_arrive(bar_g1done);
      const uint32_t* b1s = reinterpret_cast<const uint32_t*>(smem + SM_B1);
#pragma unroll
      for (int j = 0; j < 28; j++) {
        const uint32_t bw = b1s[j * 4 + (lane & 3)];
        const float bl = bflo(bw), bh = bfhi(bw);
        float h0 = gelu_tanh(bf16r(bf16r(acc[4 * j + 0]) + bl));
        float h1 = gelu_tanh(bf16r(bf16r(acc[4 * j + 1]) + bh));
        float h2 = gelu_tanh(bf16r(bf16r(acc[4 * j + 2]) + bl));
        float h3 = gelu_tanh(bf16r(bf16r(acc[4 * j + 3]) + bh));
        ha[2 * j] = pack_bf16(h0, h1);
        ha[2 * j + 1] = pack_bf16(h2, h3);
      }
    }
#pragma unroll 1
    for (int q = 0; q < NJOB; q++) {
      float acc[64];
      const uint32_t jb = sb + (q == 0 || q == 3 ? SM_X : (q == 1 ? SM_X + 65536 : SM_RING));
#pragma unroll
      for (int h = 0; h < 2; h++) {
        mbar_wait(bar_full2 + 8 * (2 * q + h), 0);
        wgmma_fence();
#pragma unroll
        for (int kk = 0; kk < 7; kk++) {
          const int kb = h * 7 + kk;
          wgmma_n128_rs(acc, ha[4 * kb], ha[4 * kb + 1], ha[4 * kb + 2], ha[4 * kb + 3],
                        make_desc(jb + h * W2_HALF + kk * 2048, 14336, 1024, 1), kb > 0);
        }
        wgmma_commit();
      }
      wgmma_wait<0>();
      if (q == 0 && elect) mbar_arrive(bar_j0done);
      uint4* dstp = g_part + ((((size_t)rt * NJOB + q) * 8 + warp) * 8 + sp) * 256 + lane;
#pragma unroll
      for (int i = 0; i < 8; i++) {
        uint4 o;
        o.x = pack_bf16(acc[8 * i + 0], acc[8 * i + 1]);
        o.y = pack_bf16(acc[8 * i + 2], acc[8 * i + 3]);
        o.z = pack_bf16(acc[8 * i + 4], acc[8 * i + 5]);
        o.w = pack_bf16(acc[8 * i + 6], acc[8 * i + 7]);
        dstp[i * 32] = o;
      }
    }
  }
}

__global__ void __launch_bounds__(256) k_final(const __nv_bfloat16* __restrict__ x, const __nv_bfloat16* __restrict__ b2,
                                               __nv_bfloat16* __restrict__ out) {
  __shared__ float2 buf[2 * FFTBUF];
  const int wg = threadIdx.x >> 7, t = threadIdx.x & 127;
  const int rt = blockIdx.x >> 3, dst = blockIdx.x & 7;
  const int row0 = blockIdx.x * 16;
  fft_phase3(row0 + wg * 8, buf + wg * FFTBUF, t, 1 + wg);
  __syncthreads();
  const int warp = threadIdx.x >> 5, lane = threadIdx.x & 31;
  const int g = lane >> 2, qd = lane & 3;
#pragma unroll 1
  for (int q = 0; q < NJOB; q++) {
    const uint4* src = g_part + (((size_t)rt * NJOB + q) * 8 + dst) * 8 * 256 + warp * 32 + lane;
    uint4 v[8];
#pragma unroll
    for (int s = 0; s < 8; s++) v[s] = __ldcg(src + s * 256);
    float o[8];
#pragma unroll
    for (int c = 0; c < 8; c++) o[c] = 0.f;
#pragma unroll
    for (int s = 0; s < 8; s++) {
      o[0] += bflo(v[s].x); o[1] += bfhi(v[s].x); o[2] += bflo(v[s].y); o[3] += bfhi(v[s].y);
      o[4] += bflo(v[s].z); o[5] += bfhi(v[s].z); o[6] += bflo(v[s].w); o[7] += bfhi(v[s].w);
    }
#pragma unroll
    for (int c = 0; c < 4; c++) {
      const int j = 2 * warp + (c >> 1);
      const int row = g + 8 * (c & 1);
      const int col = q * 128 + 8 * j + 2 * qd;
      const uint32_t bw = __ldg(reinterpret_cast<const uint32_t*>(b2 + col));
      const uint32_t xw = __ldg(reinterpret_cast<const uint32_t*>(x + (size_t)(row0 + row) * D_ + col));
      const uint32_t sw = reinterpret_cast<const uint32_t*>(buf + (row >> 3) * FFTBUF + (row & 7) * ROWP)[col >> 1];
      float r[2];
#pragma unroll
      for (int e = 0; e < 2; e++) {
        float o2 = bf16r(bf16r(o[2 * c + e]) + (e ? bfhi(bw) : bflo(bw)));
        float gg = bf16r(o2 / (1.0f + __expf(-o2)));
        float sg = bf16r((e ? bfhi(sw) : bflo(sw)) * gg);
        r[e] = (e ? bfhi(xw) : bflo(xw)) + sg;
      }
      *reinterpret_cast<uint32_t*>(out + (size_t)(row0 + row) * D_ + col) = pack_bf16(r[0], r[1]);
    }
  }
}

typedef CUresult (*EncodeFn)(CUtensorMap*, CUtensorMapDataType, cuuint32_t, void*, const cuuint64_t*, const cuuint64_t*,
                             const cuuint32_t*, const cuuint32_t*, CUtensorMapInterleave, CUtensorMapSwizzle,
                             CUtensorMapL2promotion, CUtensorMapFloatOOBfill);

}

extern "C" void kernel_launch(void* const* d_in, const int* in_sizes, int n_in, void* d_out, int out_size) {
  const __nv_bfloat16* x = (const __nv_bfloat16*)d_in[0];
  const __nv_bfloat16* wr = (const __nv_bfloat16*)d_in[1];
  const __nv_bfloat16* wi = (const __nv_bfloat16*)d_in[2];
  const __nv_bfloat16* w1 = (const __nv_bfloat16*)d_in[4];
  const __nv_bfloat16* b1 = (const __nv_bfloat16*)d_in[5];
  const __nv_bfloat16* w2 = (const __nv_bfloat16*)d_in[6];
  const __nv_bfloat16* b2 = (const __nv_bfloat16*)d_in[7];
  __nv_bfloat16* out = (__nv_bfloat16*)d_out;

  static EncodeFn enc = nullptr;
  if (!enc) {
    void* fn = nullptr;
    cudaDriverEntryPointQueryResult qr;
    cudaGetDriverEntryPoint("cuTensorMapEncodeTiled", &fn, cudaEnableDefault, &qr);
    enc = (EncodeFn)fn;
    cudaFuncSetAttribute(k_ffn, cudaFuncAttributeMaxDynamicSharedMemorySize, SM_FFN_TOTAL);
  }
  CUtensorMap m1, m2;
  {
    cuuint64_t dims[3] = {32, 512, 56};
    cuuint64_t strides[2] = {(cuuint64_t)F_ * 2, 64};
    cuuint32_t box[3] = {32, 32, 7};
    cuuint32_t es[3] = {1, 1, 1};
    enc(&m1, CU_TENSOR_MAP_DATA_TYPE_BFLOAT16, 3, (void*)w1, dims, strides, box, es, CU_TENSOR_MAP_INTERLEAVE_NONE,
        CU_TENSOR_MAP_SWIZZLE_64B, CU_TENSOR_MAP_L2_PROMOTION_L2_128B, CU_TENSOR_MAP_FLOAT_OOB_FILL_NONE);
  }
  {
    cuuint64_t dims[3] = {64, (cuuint64_t)F_, 8};
    cuuint64_t strides[2] = {(cuuint64_t)D_ * 2, 128};
    cuuint32_t box[3] = {64, 112, 2};
    cuuint32_t es[3] = {1, 1, 1};
    enc(&m2, CU_TENSOR_MAP_DATA_TYPE_BFLOAT16, 3, (void*)w2, dims, strides, box, es, CU_TENSOR_MAP_INTERLEAVE_NONE,
        CU_TENSOR_MAP_SWIZZLE_128B, CU_TENSOR_MAP_L2_PROMOTION_L2_128B, CU_TENSOR_MAP_FLOAT_OOB_FILL_NONE);
  }
  k_phase1<<<128, 256>>>(x);
  k_phase2<<<128, 256>>>(wr, wi);
  k_ffn<<<128, 288, SM_FFN_TOTAL>>>(x, b1, m1, m2);
  k_final<<<128, 256>>>(x, b2, out);
}
```

```cpp
#include <cuda_runtime.h>
#include <cuda_bf16.h>
#include <cuda.h>
#include <stdint.h>

namespace {

constexpr int S_ = 2048, D_ = 512, F_ = 1792, DF_ = 257;
constexpr int FC = 224;
constexpr int NJOB = 4;

__device__ __align__(1024) float2 g_spec[257 * 2048];
__device__ __align__(1024) uint32_t g_wt[257 * 2048];
__device__ uint4 g_part[16 * NJOB * 8 * 8 * 256];
__device__ float2 g_stats[2048];
__device__ unsigned g_bar[2];
__device__ unsigned g_flag[16 * NJOB * 8];
#define TS(i)

__device__ __forceinline__ uint32_t smem_u32(const void* p) { return (uint32_t)__cvta_generic_to_shared(p); }
__device__ __forceinline__ float bf16r(float x) { return __bfloat162float(__float2bfloat16_rn(x)); }
__device__ __forceinline__ float bflo(uint32_t w) { return __uint_as_float(w << 16); }
__device__ __forceinline__ float bfhi(uint32_t w) { return __uint_as_float(w & 0xffff0000u); }
__device__ __forceinline__ uint32_t pack_bf16(float lo, float hi) {
  uint32_t r;
  asm("cvt.rn.bf16x2.f32 %0, %1, %2;" : "=r"(r) : "f"(hi), "f"(lo));
  return r;
}
__device__ __forceinline__ uint32_t hadd2_bf16(uint32_t a, uint32_t b) {
  uint32_t r;
  asm("add.rn.bf16x2 %0, %1, %2;" : "=r"(r) : "r"(a), "r"(b));
  return r;
}
__device__ __forceinline__ void named_bar(int id, int n) { asm volatile("bar.sync %0, %1;" ::"r"(id), "r"(n) : "memory"); }
__device__ __forceinline__ void fence_async() { asm volatile("fence.proxy.async;" ::: "memory"); }

__device__ __forceinline__ void mbar_init(uint32_t bar, int cnt) { asm volatile("mbarrier.init.shared::cta.b64 [%0], %1;" ::"r"(bar), "r"(cnt) : "memory"); }
__device__ __forceinline__ void mbar_expect_tx(uint32_t bar, uint32_t bytes) { asm volatile("mbarrier.arrive.expect_tx.shared::cta.b64 _, [%0], %1;" ::"r"(bar), "r"(bytes) : "memory"); }
__device__ __forceinline__ void mbar_arrive(uint32_t bar) { asm volatile("mbarrier.arrive.shared::cta.b64 _, [%0];" ::"r"(bar) : "memory"); }
__device__ __forceinline__ bool mbar_try(uint32_t bar, uint32_t parity) {
  uint32_t ok;
  asm volatile("{\n.reg .pred p;\nmbarrier.try_wait.parity.shared::cta.b64 p, [%1], %2, %3;\nselp.u32 %0, 1, 0, p;\n}\n" : "=r"(ok) : "r"(bar), "r"(parity), "r"(20000u) : "memory");
  return ok != 0;
}
__device__ __forceinline__ void mbar_wait(uint32_t bar, uint32_t parity) {
  int it = 0;
  while (!mbar_try(bar, parity)) {
    if (++it > (1 << 17)) __trap();
  }
}
__device__ __forceinline__ void tma_load_3d(uint32_t dst, const CUtensorMap* map, int c0, int c1, int c2, uint32_t bar) {
  asm volatile("cp.async.bulk.tensor.3d.shared::cluster.global.mbarrier::complete_tx::bytes [%0], [%1, {%3, %4, %5}], [%2];"
               ::"r"(dst), "l"((uint64_t)map), "r"(bar), "r"(c0), "r"(c1), "r"(c2) : "memory");
}
__device__ __forceinline__ void tma_load_2d(uint32_t dst, const CUtensorMap* map, int c0, int c1, uint32_t bar) {
  asm volatile("cp.async.bulk.tensor.2d.shared::cluster.global.mbarrier::complete_tx::bytes [%0], [%1, {%3, %4}], [%2];"
               ::"r"(dst), "l"((uint64_t)map), "r"(bar), "r"(c0), "r"(c1) : "memory");
}
__device__ __forceinline__ void tma_store_2d(const CUtensorMap* map, int c0, int c1, uint32_t src) {
  asm volatile("cp.async.bulk.tensor.2d.global.shared::cta.bulk_group [%0, {%2, %3}], [%1];"
               ::"l"((uint64_t)map), "r"(src), "r"(c0), "r"(c1) : "memory");
}
__device__ __forceinline__ void tma_store_commit_wait() {
  asm volatile("cp.async.bulk.commit_group;" ::: "memory");
  asm volatile("cp.async.bulk.wait_group 0;" ::: "memory");
}
__device__ __forceinline__ void wgmma_fence() { asm volatile("wgmma.fence.sync.aligned;" ::: "memory"); }
__device__ __forceinline__ void wgmma_commit() { asm volatile("wgmma.commit_group.sync.aligned;" ::: "memory"); }
template <int N> __device__ __forceinline__ void wgmma_wait() { asm volatile("wgmma.wait_group.sync.aligned %0;" ::"n"(N) : "memory"); }
__device__ __forceinline__ uint64_t make_desc(uint32_t addr, uint32_t lbo_bytes, uint32_t sbo_bytes, uint32_t swz) {
  uint64_t d = 0;
  d |= (uint64_t)((addr & 0x3FFFF) >> 4);
  d |= (uint64_t)((lbo_bytes & 0x3FFFF) >> 4) << 16;
  d |= (uint64_t)((sbo_bytes & 0x3FFFF) >> 4) << 32;
  d |= (uint64_t)swz << 62;
  return d;
}
__device__ __forceinline__ unsigned ld_acquire(const unsigned* p) {
  unsigned v;
  asm volatile("ld.acquire.gpu.global.u32 %0, [%1];" : "=r"(v) : "l"(p) : "memory");
  return v;
}

__device__ __forceinline__ void wgmma_n224_ss(float (&d)[112], uint64_t da, uint64_t db, int scale_d) {
  asm volatile("{\n.reg .pred p;\nsetp.ne.b32 p, %114, 0;\n"
    "wgmma.mma_async.sync.aligned.m64n224k16.f32.bf16.bf16 {%0, %1, %2, %3, %4, %5, %6, %7, %8, %9, %10, %11, %12, %13, %14, %15, %16, %17, %18, %19, %20, %21, %22, %23, %24, %25, %26, %27, %28, %29, %30, %31, %32, %33, %34, %35, %36, %37, %38, %39, %40, %41, %42, %43, %44, %45, %46, %47, %48, %49, %50, %51, %52, %53, %54, %55, %56, %57, %58, %59, %60, %61, %62, %63, %64, %65, %66, %67, %68, %69, %70, %71, %72, %73, %74, %75, %76, %77, %78, %79, %80, %81, %82, %83, %84, %85, %86, %87, %88, %89, %90, %91, %92, %93, %94, %95, %96, %97, %98, %99, %100, %101, %102, %103, %104, %105, %106, %107, %108, %109, %110, %111}, %112, %113, p, 1, 1, 0, 1;\n}\n"
    : "+f"(d[0]), "+f"(d[1]), "+f"(d[2]), "+f"(d[3]), "+f"(d[4]), "+f"(d[5]), "+f"(d[6]), "+f"(d[7]), "+f"(d[8]), "+f"(d[9]), "+f"(d[10]), "+f"(d[11]), "+f"(d[12]), "+f"(d[13]), "+f"(d[14]), "+f"(d[15]), "+f"(d[16]), "+f"(d[17]), "+f"(d[18]), "+f"(d[19]), "+f"(d[20]), "+f"(d[21]), "+f"(d[22]), "+f"(d[23]), "+f"(d[24]), "+f"(d[25]), "+f"(d[26]), "+f"(d[27]), "+f"(d[28]), "+f"(d[29]), "+f"(d[30]), "+f"(d[31]), "+f"(d[32]), "+f"(d[33]), "+f"(d[34]), "+f"(d[35]), "+f"(d[36]), "+f"(d[37]), "+f"(d[38]), "+f"(d[39]), "+f"(d[40]), "+f"(d[41]), "+f"(d[42]), "+f"(d[43]), "+f"(d[44]), "+f"(d[45]), "+f"(d[46]), "+f"(d[47]), "+f"(d[48]), "+f"(d[49]), "+f"(d[50]), "+f"(d[51]), "+f"(d[52]), "+f"(d[53]), "+f"(d[54]), "+f"(d[55]), "+f"(d[56]), "+f"(d[57]), "+f"(d[58]), "+f"(d[59]), "+f"(d[60]), "+f"(d[61]), "+f"(d[62]), "+f"(d[63]), "+f"(d[64]), "+f"(d[65]), "+f"(d[66]), "+f"(d[67]), "+f"(d[68]), "+f"(d[69]), "+f"(d[70]), "+f"(d[71]), "+f"(d[72]), "+f"(d[73]), "+f"(d[74]), "+f"(d[75]), "+f"(d[76]), "+f"(d[77]), "+f"(d[78]), "+f"(d[79]), "+f"(d[80]), "+f"(d[81]), "+f"(d[82]), "+f"(d[83]), "+f"(d[84]), "+f"(d[85]), "+f"(d[86]), "+f"(d[87]), "+f"(d[88]), "+f"(d[89]), "+f"(d[90]), "+f"(d[91]), "+f"(d[92]), "+f"(d[93]), "+f"(d[94]), "+f"(d[95]), "+f"(d[96]), "+f"(d[97]), "+f"(d[98]), "+f"(d[99]), "+f"(d[100]), "+f"(d[101]), "+f"(d[102]), "+f"(d[103]), "+f"(d[104]), "+f"(d[105]), "+f"(d[106]), "+f"(d[107]), "+f"(d[108]), "+f"(d[109]), "+f"(d[110]), "+f"(d[111])
    : "l"(da), "l"(db), "r"(scale_d));
}
__device__ __forceinline__ void wgmma_n128_ss(float (&d)[64], uint64_t da, uint64_t db, int scale_d) {
  asm volatile("{\n.reg .pred p;\nsetp.ne.b32 p, %66, 0;\n"
    "wgmma.mma_async.sync.aligned.m64n128k16.f32.bf16.bf16 {%0, %1, %2, %3, %4, %5, %6, %7, %8, %9, %10, %11, %12, %13, %14, %15, %16, %17, %18, %19, %20, %21, %22, %23, %24, %25, %26, %27, %28, %29, %30, %31, %32, %33, %34, %35, %36, %37, %38, %39, %40, %41, %42, %43, %44, %45, %46, %47, %48, %49, %50, %51, %52, %53, %54, %55, %56, %57, %58, %59, %60, %61, %62, %63}, %64, %65, p, 1, 1, 0, 1;\n}\n"
    : "+f"(d[0]), "+f"(d[1]), "+f"(d[2]), "+f"(d[3]), "+f"(d[4]), "+f"(d[5]), "+f"(d[6]), "+f"(d[7]), "+f"(d[8]), "+f"(d[9]), "+f"(d[10]), "+f"(d[11]), "+f"(d[12]), "+f"(d[13]), "+f"(d[14]), "+f"(d[15]), "+f"(d[16]), "+f"(d[17]), "+f"(d[18]), "+f"(d[19]), "+f"(d[20]), "+f"(d[21]), "+f"(d[22]), "+f"(d[23]), "+f"(d[24]), "+f"(d[25]), "+f"(d[26]), "+f"(d[27]), "+f"(d[28]), "+f"(d[29]), "+f"(d[30]), "+f"(d[31]), "+f"(d[32]), "+f"(d[33]), "+f"(d[34]), "+f"(d[35]), "+f"(d[36]), "+f"(d[37]), "+f"(d[38]), "+f"(d[39]), "+f"(d[40]), "+f"(d[41]), "+f"(d[42]), "+f"(d[43]), "+f"(d[44]), "+f"(d[45]), "+f"(d[46]), "+f"(d[47]), "+f"(d[48]), "+f"(d[49]), "+f"(d[50]), "+f"(d[51]), "+f"(d[52]), "+f"(d[53]), "+f"(d[54]), "+f"(d[55]), "+f"(d[56]), "+f"(d[57]), "+f"(d[58]), "+f"(d[59]), "+f"(d[60]), "+f"(d[61]), "+f"(d[62]), "+f"(d[63])
    : "l"(da), "l"(db), "r"(scale_d));
}
__device__ __forceinline__ void wgmma_n96_ss(float (&d)[48], uint64_t da, uint64_t db, int scale_d) {
  asm volatile("{\n.reg .pred p;\nsetp.ne.b32 p, %50, 0;\n"
    "wgmma.mma_async.sync.aligned.m64n96k16.f32.bf16.bf16 {%0, %1, %2, %3, %4, %5, %6, %7, %8, %9, %10, %11, %12, %13, %14, %15, %16, %17, %18, %19, %20, %21, %22, %23, %24, %25, %26, %27, %28, %29, %30, %31, %32, %33, %34, %35, %36, %37, %38, %39, %40, %41, %42, %43, %44, %45, %46, %47}, %48, %49, p, 1, 1, 0, 1;\n}\n"
    : "+f"(d[0]), "+f"(d[1]), "+f"(d[2]), "+f"(d[3]), "+f"(d[4]), "+f"(d[5]), "+f"(d[6]), "+f"(d[7]), "+f"(d[8]), "+f"(d[9]), "+f"(d[10]), "+f"(d[11]), "+f"(d[12]), "+f"(d[13]), "+f"(d[14]), "+f"(d[15]), "+f"(d[16]), "+f"(d[17]), "+f"(d[18]), "+f"(d[19]), "+f"(d[20]), "+f"(d[21]), "+f"(d[22]), "+f"(d[23]), "+f"(d[24]), "+f"(d[25]), "+f"(d[26]), "+f"(d[27]), "+f"(d[28]), "+f"(d[29]), "+f"(d[30]), "+f"(d[31]), "+f"(d[32]), "+f"(d[33]), "+f"(d[34]), "+f"(d[35]), "+f"(d[36]), "+f"(d[37]), "+f"(d[38]), "+f"(d[39]), "+f"(d[40]), "+f"(d[41]), "+f"(d[42]), "+f"(d[43]), "+f"(d[44]), "+f"(d[45]), "+f"(d[46]), "+f"(d[47])
    : "l"(da), "l"(db), "r"(scale_d));
}
__device__ __forceinline__ void wgmma_n128_rs(float (&d)[64], uint32_t a0, uint32_t a1, uint32_t a2, uint32_t a3, uint64_t db, int scale_d) {
  asm volatile("{\n.reg .pred p;\nsetp.ne.b32 p, %69, 0;\n"
    "wgmma.mma_async.sync.aligned.m64n128k16.f32.bf16.bf16 {%0, %1, %2, %3, %4, %5, %6, %7, %8, %9, %10, %11, %12, %13, %14, %15, %16, %17, %18, %19, %20, %21, %22, %23, %24, %25, %26, %27, %28, %29, %30, %31, %32, %33, %34, %35, %36, %37, %38, %39, %40, %41, %42, %43, %44, %45, %46, %47, %48, %49, %50, %51, %52, %53, %54, %55, %56, %57, %58, %59, %60, %61, %62, %63}, {%64, %65, %66, %67}, %68, p, 1, 1, 1;\n}\n"
    : "+f"(d[0]), "+f"(d[1]), "+f"(d[2]), "+f"(d[3]), "+f"(d[4]), "+f"(d[5]), "+f"(d[6]), "+f"(d[7]), "+f"(d[8]), "+f"(d[9]), "+f"(d[10]), "+f"(d[11]), "+f"(d[12]), "+f"(d[13]), "+f"(d[14]), "+f"(d[15]), "+f"(d[16]), "+f"(d[17]), "+f"(d[18]), "+f"(d[19]), "+f"(d[20]), "+f"(d[21]), "+f"(d[22]), "+f"(d[23]), "+f"(d[24]), "+f"(d[25]), "+f"(d[26]), "+f"(d[27]), "+f"(d[28]), "+f"(d[29]), "+f"(d[30]), "+f"(d[31]), "+f"(d[32]), "+f"(d[33]), "+f"(d[34]), "+f"(d[35]), "+f"(d[36]), "+f"(d[37]), "+f"(d[38]), "+f"(d[39]), "+f"(d[40]), "+f"(d[41]), "+f"(d[42]), "+f"(d[43]), "+f"(d[44]), "+f"(d[45]), "+f"(d[46]), "+f"(d[47]), "+f"(d[48]), "+f"(d[49]), "+f"(d[50]), "+f"(d[51]), "+f"(d[52]), "+f"(d[53]), "+f"(d[54]), "+f"(d[55]), "+f"(d[56]), "+f"(d[57]), "+f"(d[58]), "+f"(d[59]), "+f"(d[60]), "+f"(d[61]), "+f"(d[62]), "+f"(d[63])
    : "r"(a0), "r"(a1), "r"(a2), "r"(a3), "l"(db), "r"(scale_d));
}

__device__ __forceinline__ float2 cadd(float2 a, float2 b) { return make_float2(a.x + b.x, a.y + b.y); }
__device__ __forceinline__ float2 csub(float2 a, float2 b) { return make_float2(a.x - b.x, a.y - b.y); }
__device__ __forceinline__ float2 cmul(float2 a, float2 b) { return make_float2(a.x * b.x - a.y * b.y, a.x * b.y + a.y * b.x); }
__device__ __forceinline__ float2 cconj(float2 a) { return make_float2(a.x, -a.y); }

template <int DIR> __device__ __forceinline__ void dft4(float2& a0, float2& a1, float2& a2, float2& a3) {
  float2 t0 = cadd(a0, a2), t1 = csub(a0, a2), t2 = cadd(a1, a3), t3 = csub(a1, a3);
  float2 t3r = DIR < 0 ? make_float2(t3.y, -t3.x) : make_float2(-t3.y, t3.x);
  a0 = cadd(t0, t2); a2 = csub(t0, t2); a1 = cadd(t1, t3r); a3 = csub(t1, t3r);
}
template <int DIR> __device__ __forceinline__ float2 mulw(float2 v, float c, float s) {
  return DIR < 0 ? make_float2(v.x * c + v.y * s, v.y * c - v.x * s) : make_float2(v.x * c - v.y * s, v.y * c + v.x * s);
}
template <int DIR> __device__ __forceinline__ float2 muli(float2 v) {
  return DIR < 0 ? make_float2(v.y, -v.x) : make_float2(-v.y, v.x);
}
#define O16(k) (4 * ((k) & 3) + ((k) >> 2))
#define O8(k) (2 * ((k) & 3) + ((k) >> 2))
template <int DIR> __device__ __forceinline__ void dft16(float2 (&v)[16]) {
  constexpr float C1 = 0.92387953251128674f, S1 = 0.38268343236508977f, R = 0.70710678118654752f;
#pragma unroll
  for (int n2 = 0; n2 < 4; n2++) dft4<DIR>(v[n2], v[4 + n2], v[8 + n2], v[12 + n2]);
  v[5] = mulw<DIR>(v[5], C1, S1);
  v[6] = mulw<DIR>(v[6], R, R);
  v[7] = mulw<DIR>(v[7], S1, C1);
  v[9] = mulw<DIR>(v[9], R, R);
  v[10] = muli<DIR>(v[10]);
  v[11] = mulw<DIR>(v[11], -R, R);
  v[13] = mulw<DIR>(v[13], S1, C1);
  v[14] = mulw<DIR>(v[14], -R, R);
  v[15] = mulw<DIR>(v[15], -C1, -S1);
#pragma unroll
  for (int k1 = 0; k1 < 4; k1++) dft4<DIR>(v[4 * k1], v[4 * k1 + 1], v[4 * k1 + 2], v[4 * k1 + 3]);
}
template <int DIR> __device__ __forceinline__ void dft8(float2 (&v)[8]) {
  constexpr float R = 0.70710678118654752f;
  dft4<DIR>(v[0], v[2], v[4], v[6]);
  dft4<DIR>(v[1], v[3], v[5], v[7]);
  v[3] = mulw<DIR>(v[3], R, R);
  v[5] = muli<DIR>(v[5]);
  v[7] = mulw<DIR>(v[7], -R, R);
#pragma unroll
  for (int k1 = 0; k1 < 4; k1++) {
    float2 a = v[2 * k1], b = v[2 * k1 + 1];
    v[2 * k1] = cadd(a, b); v[2 * k1 + 1] = csub(a, b);
  }
}
template <int N> __device__ __forceinline__ float2 twcs(int m) {
  m &= (N - 1);
  if (m >= N / 2) m -= N;
  float s, c;
  __sincosf((float)m * (6.283185307179586f / N), &s, &c);
  return make_float2(c, s);
}

__device__ __forceinline__ float2* tile_at(uint8_t* tile, int k, int r) {
  return reinterpret_cast<float2*>(tile + k * 128 + ((((r >> 1) ^ k) & 7) << 4) + (r & 1) * 8);
}
constexpr int SPITCH = 260;

__device__ __forceinline__ void tile_fft256(uint8_t* tile, int t, int barid) {
  const int r = t & 15, q = t >> 4;
  float2 v[16];
#pragma unroll
  for (int n1 = 0; n1 < 16; n1++) v[n1] = *tile_at(tile, 16 * n1 + q, r);
  dft16<-1>(v);
#pragma unroll
  for (int k1 = 0; k1 < 16; k1++) {
    float2 u = v[O16(k1)];
    if (k1) { const float2 tw = twcs<256>(q * k1); u = mulw<-1>(u, tw.x, tw.y); }
    *tile_at(tile, 16 * k1 + q, r) = u;
  }
  named_bar(barid, 256);
#pragma unroll
  for (int j = 0; j < 16; j++) v[j] = *tile_at(tile, 16 * q + j, r);
  dft16<-1>(v);
  named_bar(barid, 256);
#pragma unroll
  for (int k2 = 0; k2 < 16; k2++) *tile_at(tile, q + 16 * k2, r) = v[O16(k2)];
  named_bar(barid, 256);
}

__device__ __forceinline__ void fft_ln(const __nv_bfloat16* __restrict__ x, int s0, uint8_t* tile, int t, int barid) {
  const int rr = t >> 4, n2 = t & 15;
  uint32_t w[16];
  const uint32_t* xw = reinterpret_cast<const uint32_t*>(x + (size_t)(s0 + rr) * D_);
#pragma unroll
  for (int n1 = 0; n1 < 16; n1++) w[n1] = __ldg(xw + 16 * n1 + n2);
  float sum = 0.f;
#pragma unroll
  for (int n1 = 0; n1 < 16; n1++) sum += bflo(w[n1]) + bfhi(w[n1]);
#pragma unroll
  for (int o = 1; o < 16; o <<= 1) sum += __shfl_xor_sync(0xffffffffu, sum, o);
  const float mean = sum * (1.0f / D_);
  float sq = 0.f;
#pragma unroll
  for (int n1 = 0; n1 < 16; n1++) {
    float a = bflo(w[n1]) - mean, c = bfhi(w[n1]) - mean;
    sq += a * a + c * c;
  }
#pragma unroll
  for (int o = 1; o < 16; o <<= 1) sq += __shfl_xor_sync(0xffffffffu, sq, o);
  const float mb = bf16r(mean);
  float sd, rs;
  asm("sqrt.approx.f32 %0, %1;" : "=f"(sd) : "f"(bf16r(bf16r(sq * (1.0f / D_)) + 1e-5f)));
  asm("rcp.approx.f32 %0, %1;" : "=f"(rs) : "f"(bf16r(sd)));
  if (n2 == 0) g_stats[s0 + rr] = make_float2(mb, rs);
#pragma unroll
  for (int n1 = 0; n1 < 16; n1++)
    *tile_at(tile, 16 * n1 + n2, rr) = make_float2(bf16r(bf16r(bflo(w[n1]) - mb) * rs), bf16r(bf16r(bfhi(w[n1]) - mb) * rs));
  named_bar(barid, 256);
}

__device__ __forceinline__ void fft_post(uint8_t* tile, int s0, int t) {
  const int r = t & 15, q = t >> 4;
#pragma unroll 4
  for (int i = 0; i < 8; i++) {
    const int j = q + 16 * i;
    float2* pa = tile_at(tile, j, r);
    float2* pb = tile_at(tile, j == 0 ? 128 : 256 - j, r);
    const float2 A = *pa, Zb = *pb;
    if (j == 0) {
      *pa = make_float2(A.x + A.y, 0.f);
      g_spec[(size_t)256 * S_ + s0 + r] = make_float2(A.x - A.y, 0.f);
      *pb = cconj(Zb);
    } else {
      const float2 B = cconj(Zb);
      const float2 E = make_float2(0.5f * (A.x + B.x), 0.5f * (A.y + B.y));
      const float2 O = make_float2(0.5f * (A.y - B.y), -0.5f * (A.x - B.x));
      const float2 tw = twcs<512>(j);
      const float2 T = mulw<-1>(O, tw.x, tw.y);
      *pa = cadd(E, T);
      *pb = cconj(csub(E, T));
    }
  }
}

__device__ __forceinline__ void fft_phase2(int slot0, int slot1, float2* buf, int t, int barid) {
  float2* col0 = g_spec + (size_t)slot0 * S_;
  float2* col1 = g_spec + (size_t)slot1 * S_;
  float2* buf1 = buf + 2048;
  float2 v[2][16];
#pragma unroll
  for (int n1 = 0; n1 < 16; n1++) { v[0][n1] = __ldcg(col0 + 128 * n1 + t); v[1][n1] = __ldcg(col1 + 128 * n1 + t); }
  uint32_t wq[2][16];
#pragma unroll
  for (int i = 0; i < 16; i++) {
    wq[0][i] = __ldcg(g_wt + (size_t)slot0 * S_ + t + 128 * i);
    wq[1][i] = __ldcg(g_wt + (size_t)slot1 * S_ + t + 128 * i);
  }
  const int k1 = t >> 3, m2 = t & 7;
  const int sw = (t >> 1) & 7;
#pragma unroll 1
  for (int it = 0; it < 2; it++) {
    dft16<-1>(v[0]);
    dft16<-1>(v[1]);
#pragma unroll
    for (int kk = 0; kk < 16; kk++) {
      float2 u0 = v[0][O16(kk)], u1 = v[1][O16(kk)];
      if (kk) {
        const float2 tw = twcs<2048>(t * kk);
        u0 = mulw<-1>(u0, tw.x, tw.y); u1 = mulw<-1>(u1, tw.x, tw.y);
      }
      const int a = kk * 128 + (t ^ ((kk & 1) << 3));
      buf[a] = u0;
      buf1[a] = u1;
    }
    named_bar(barid, 128);
#pragma unroll
    for (int m1 = 0; m1 < 16; m1++) {
      const int a = k1 * 128 + ((8 * m1 + m2) ^ ((k1 & 1) << 3));
      v[0][m1] = buf[a]; v[1][m1] = buf1[a];
    }
    named_bar(barid, 128);
    dft16<-1>(v[0]);
    dft16<-1>(v[1]);
#pragma unroll
    for (int j1 = 0; j1 < 16; j1++) {
      float2 u0 = v[0][O16(j1)], u1 = v[1][O16(j1)];
      if (j1) {
        const float2 tw = twcs<128>(m2 * j1);
        u0 = mulw<-1>(u0, tw.x, tw.y); u1 = mulw<-1>(u1, tw.x, tw.y);
      }
      const int p = j1 * 16 + k1;
      const int a = p * 8 + (m2 ^ ((p >> 1) & 7));
      buf[a] = u0;
      buf1[a] = u1;
    }
    named_bar(barid, 128);
    float2 c[2][2][8];
#pragma unroll
    for (int m = 0; m < 8; m++) {
      c[0][0][m] = buf[t * 8 + (m ^ sw)];
      c[0][1][m] = buf[(t + 128) * 8 + (m ^ sw)];
      c[1][0][m] = buf1[t * 8 + (m ^ sw)];
      c[1][1][m] = buf1[(t + 128) * 8 + (m ^ sw)];
    }
    named_bar(barid, 128);
#pragma unroll
    for (int b = 0; b < 2; b++) { dft8<-1>(c[b][0]); dft8<-1>(c[b][1]); }
    if (it == 0) {
      constexpr float SC = 1.0f / (2048.0f * 512.0f);
#pragma unroll
      for (int b = 0; b < 2; b++)
#pragma unroll
        for (int i = 0; i < 16; i++)
          v[b][i] = cconj(cmul(c[b][i & 1][O8(i >> 1)], make_float2(bflo(wq[b][i]) * SC, bfhi(wq[b][i]) * SC)));
    } else {
#pragma unroll
      for (int i = 0; i < 16; i++) {
        col0[128 * i + t] = cconj(c[0][i & 1][O8(i >> 1)]);
        col1[128 * i + t] = cconj(c[1][i & 1][O8(i >> 1)]);
      }
    }
  }
}

__device__ __forceinline__ void fft_pre(uint8_t* tile, float y256, int t, int barid) {
  const int r = t & 15, q = t >> 4;
#pragma unroll 4
  for (int i = 0; i < 8; i++) {
    const int j = q + 16 * i;
    float2* pa = tile_at(tile, j, r);
    float2* pb = tile_at(tile, j == 0 ? 128 : 256 - j, r);
    const float2 yk = *pa, ym = *pb;
    if (j == 0) {
      *pa = make_float2(yk.x + y256, y256 - yk.x);
      *pb = make_float2(2.f * ym.x, 2.f * ym.y);
    } else {
      const float2 c = cconj(ym);
      const float2 Sx = cadd(yk, c), Dx = csub(yk, c);
      const float2 tw = twcs<512>(j);
      const float2 T = mulw<1>(Dx, tw.x, tw.y);
      const float2 iT = make_float2(-T.y, T.x);
      *pa = cconj(cadd(Sx, iT));
      *pb = csub(Sx, iT);
    }
  }
  named_bar(barid, 256);
}

constexpr int SM_X = 0;
constexpr int SM_RING = 131072;
constexpr int W1_STAGE = 14336;
constexpr int W2_HALF = 28672;
constexpr int SM_FFT = SM_RING + 4 * W1_STAGE;
constexpr int SM_WT = SM_FFT + 32768;
constexpr int SM_B1 = SM_WT + 8192;
constexpr int SM_CS = SM_B1 + 512;
constexpr int SM_BAR = SM_CS + 2 * FC * 4;
constexpr int SM_TOTAL = SM_BAR + 256;
constexpr int NTHREADS = 384;

__device__ __forceinline__ float gelu_tanh(float x) {
  float u = x * (0.7978845608028654f + 0.035677408136300125f * x * x);
  float th;
  asm("tanh.approx.f32 %0, %1;" : "=f"(th) : "f"(u));
  float hx = 0.5f * x;
  return fmaf(hx, th, hx);
}
__device__ __forceinline__ unsigned grid_arrive(unsigned* cnt) {
  __threadfence();
  unsigned old = atomicAdd(cnt, 1u);
  return (old / 129u + 1u) * 129u;
}
__device__ __forceinline__ void grid_wait(const unsigned* cnt, unsigned target) {
  int it = 0;
  while ((int)(ld_acquire(cnt) - target) < 0) {
    if (++it > (1 << 22)) __trap();
  }
}

struct Maps { CUtensorMap x, w1, w2, spec, wt; };

__global__ void __launch_bounds__(NTHREADS, 1)
k_mega(const __nv_bfloat16* __restrict__ x, const __nv_bfloat16* __restrict__ wr, const __nv_bfloat16* __restrict__ wi,
       const __nv_bfloat16* __restrict__ b1, const __nv_bfloat16* __restrict__ b2, __nv_bfloat16* __restrict__ out,
       const __grid_constant__ Maps maps) {
  extern __shared__ __align__(1024) uint8_t smem[];
  const uint32_t sb = smem_u32(smem);
  const int rt = blockIdx.x >> 3, sp = blockIdx.x & 7;
  const int warp = threadIdx.x >> 5, lane = threadIdx.x & 31;
  if (threadIdx.x == 0) TS(0);
  const uint32_t bar_full1 = sb + SM_BAR;
  const uint32_t bar_full2 = sb + SM_BAR + 64;
  const uint32_t bar_xfull = sb + SM_BAR + 128;
  unsigned* relcnt = reinterpret_cast<unsigned*>(smem + SM_BAR + 192);
  const uint32_t bar_stats = sb + SM_BAR + 216;
  const uint32_t bar_p1 = sb + SM_BAR + 224;
  const uint32_t bar_tile = sb + SM_BAR + 240;
  if (threadIdx.x == 0) {
    for (int i = 0; i < 4; i++) mbar_init(bar_full1 + 8 * i, 1);
    for (int i = 0; i < 8; i++) { mbar_init(bar_full2 + 8 * i, 1); mbar_init(bar_xfull + 8 * i, 1); }
    mbar_init(bar_stats, 1); mbar_init(bar_p1, 256); mbar_init(bar_tile, 1);
    for (int i = 0; i < 6; i++) relcnt[i] = 0;
    asm volatile("fence.mbarrier_init.release.cluster;" ::: "memory");
    for (int ks = 0; ks < (blockIdx.x < 128 ? 8 : 0); ks++) {
      mbar_expect_tx(bar_xfull + 8 * ks, 16384);
      tma_load_2d(sb + SM_X + ks * 16384, &maps.x, ks * 64, rt * 128, bar_xfull + 8 * ks);
      if (ks < 4) {
        mbar_expect_tx(bar_full1 + 8 * ks, W1_STAGE);
        tma_load_3d(sb + SM_RING + ks * W1_STAGE, &maps.w1, 0, ks * 32, sp * 7, bar_full1 + 8 * ks);
      }
    }
  }
  __syncthreads();

  if (warp >= 8) {
    const int t = threadIdx.x & 127;
    const int barid = 3;
    const int s0 = blockIdx.x * 16;
    const bool extra = blockIdx.x == 128;
    if (!extra) {
      const int fwp = warp - 8;
      uint32_t wv[2][16];
#pragma unroll
      for (int rd = 0; rd < 2; rd++) {
        const unsigned short* pr = reinterpret_cast<const unsigned short*>(wr) + (size_t)s0 * DF_ + rd * 128 + fwp * 32 + lane;
        const unsigned short* pi = reinterpret_cast<const unsigned short*>(wi) + (size_t)s0 * DF_ + rd * 128 + fwp * 32 + lane;
#pragma unroll
        for (int u = 0; u < 16; u++) wv[rd][u] = (uint32_t)__ldg(pr + u * DF_) | ((uint32_t)__ldg(pi + u * DF_) << 16);
      }
      if (t < 16) {
        const size_t o = (size_t)(s0 + t) * DF_ + 256;
        g_wt[(size_t)256 * S_ + s0 + t] = (uint32_t)__ldg(reinterpret_cast<const unsigned short*>(wr) + o) |
                                          ((uint32_t)__ldg(reinterpret_cast<const unsigned short*>(wi) + o) << 16);
      }
      const uint32_t stg = (uint32_t)(SM_WT + fwp * 2048);
#pragma unroll
      for (int rd = 0; rd < 2; rd++) {
#pragma unroll
        for (int c = 0; c < 4; c++)
          *reinterpret_cast<uint4*>(smem + stg + lane * 64 + ((c ^ ((lane >> 1) & 3)) << 4)) =
              make_uint4(wv[rd][4 * c], wv[rd][4 * c + 1], wv[rd][4 * c + 2], wv[rd][4 * c + 3]);
        fence_async();
        __syncwarp();
        if (lane == 0) {
          tma_store_2d(&maps.wt, s0, rd * 128 + fwp * 32, sb + stg);
          asm volatile("cp.async.bulk.commit_group;" ::: "memory");
          if (rd == 0) asm volatile("cp.async.bulk.wait_group.read 0;" ::: "memory");
          else { asm volatile("cp.async.bulk.wait_group 0;" ::: "memory"); __threadfence(); }
        }
        __syncwarp();
      }
    }
    named_bar(barid, 128);
    if (t == 0) {
      TS(11);
      if (!extra) {
        mbar_wait(bar_p1, 0);
        tma_store_2d(&maps.spec, s0, 0, sb + SM_FFT);
        tma_store_commit_wait();
      }
      TS(12);
      const unsigned target = grid_arrive(&g_bar[0]);
      grid_wait(&g_bar[0], target);
      mbar_arrive(bar_stats);
    }
    named_bar(barid, 128);
    if (t == 0) TS(13);
    fft_phase2(extra ? 256 : blockIdx.x * 2, extra ? 256 : blockIdx.x * 2 + 1, reinterpret_cast<float2*>(smem + SM_FFT), t, barid);
    named_bar(barid, 128);
    if (t == 0) {
      TS(14);
      const unsigned target = grid_arrive(&g_bar[1]);
      if (!extra) {
        grid_wait(&g_bar[1], target);
        TS(15);
        fence_async();
        mbar_expect_tx(bar_tile, 32768);
        tma_load_2d(sb + SM_FFT, &maps.spec, s0, 0, bar_tile);
      }
    }
  } else {
    if (blockIdx.x == 128) return;
    const int wg = warp >> 2, tt = threadIdx.x & 127;
    uint8_t* tile = smem + SM_FFT;
    if (wg == 0 && tt < 112) reinterpret_cast<uint32_t*>(smem + SM_B1)[tt] = __ldg(reinterpret_cast<const uint32_t*>(b1 + sp * FC) + tt);
    fft_ln(x, blockIdx.x * 16, tile, threadIdx.x, 1);
    if (threadIdx.x == 0) TS(9);
    tile_fft256(tile, threadIdx.x, 1);
    if (threadIdx.x == 0) TS(10);
    fft_post(tile, blockIdx.x * 16, threadIdx.x);
    fence_async();
    __threadfence();
    mbar_arrive(bar_p1);
    auto load_w2 = [&](int q, uint32_t dst) {
      for (int h = 0; h < 2; h++) {
        mbar_expect_tx(bar_full2 + 8 * (2 * q + h), W2_HALF);
        tma_load_3d(dst + h * W2_HALF, &maps.w2, 0, sp * FC + h * 112, 2 * q, bar_full2 + 8 * (2 * q + h));
      }
    };
    auto release1 = [&](int ks) {
      __syncwarp();
      if (lane == 0) {
        __threadfence_block();
        const unsigned old = atomicAdd(&relcnt[ks & 3], 1u);
        if ((old & 7u) == 7u) {
          __threadfence_block();
          const int s = ks & 3;
          if (ks + 4 < 16) {
            mbar_expect_tx(bar_full1 + 8 * s, W1_STAGE);
            tma_load_3d(sb + SM_RING + s * W1_STAGE, &maps.w1, 0, (ks + 4) * 32, sp * 7, bar_full1 + 8 * s);
          }
          if (ks == 7) load_w2(0, sb + SM_X);
          if (ks == 15) { load_w2(1, sb + SM_X + 65536); load_w2(2, sb + SM_RING); }
        }
      }
    };
    uint32_t ha[56];
    {
      float acc[112];
#pragma unroll
      for (int i = 0; i < 112; i++) acc[i] = 0.f;
      float cs0 = 0.f, cs1 = 0.f;
      const uint32_t cs_base = (uint32_t)(tt >> 4) * 2048 + (uint32_t)wg * 1024 + (uint32_t)(tt & 3) * 4;
      const uint32_t cs_c = (tt >> 2) & 3;
#pragma unroll 1
      for (int ks = 0; ks < 16; ks++) {
        const int s = ks & 3;
        if (!(ks & 1)) mbar_wait(bar_xfull + 8 * (ks >> 1), 0);
        mbar_wait(bar_full1 + 8 * s, (ks >> 2) & 1);
        if (threadIdx.x == 0 && ks == 0) TS(1);
        if (threadIdx.x == 0 && (ks & 1)) TS(24 + (ks >> 1));
        wgmma_fence();
#pragma unroll
        for (int kk = 0; kk < 2; kk++) {
          const uint32_t aaddr = sb + SM_X + (ks >> 1) * 16384 + wg * 8192 + (ks & 1) * 64 + kk * 32;
          const uint32_t baddr = sb + SM_RING + s * W1_STAGE + kk * 1024;
          wgmma_n224_ss(acc, make_desc(aaddr, 16, 1024, 1), make_desc(baddr, 2048, 512, 2), 1);
        }
        wgmma_commit();
        if (tt < 112) {
          const uint8_t* st = smem + SM_RING + s * W1_STAGE + cs_base;
#pragma unroll
          for (int k = 0; k < 16; k++) {
            const uint32_t w = *reinterpret_cast<const uint32_t*>(st + k * 64 + ((cs_c ^ ((k >> 1) & 3)) << 4));
            cs0 += bflo(w); cs1 += bfhi(w);
          }
        }
        if (ks > 0) {
          wgmma_wait<1>();
          release1(ks - 1);
        }
      }
      if (tt < 112) *reinterpret_cast<float2*>(smem + SM_CS + wg * FC * 4 + tt * 8) = make_float2(cs0, cs1);
      wgmma_wait<0>();
      release1(15);
      if (threadIdx.x == 0) TS(2);
      named_bar(1, 256);
      mbar_wait(bar_stats, 0);
      const int row = rt * 128 + warp * 16 + (lane >> 2);
      const float2 st0 = __ldcg(&g_stats[row]), st1 = __ldcg(&g_stats[row + 8]);
      if (threadIdx.x == 0) TS(3);
      const uint32_t* b1s = reinterpret_cast<const uint32_t*>(smem + SM_B1);
      const float2* csa = reinterpret_cast<const float2*>(smem + SM_CS);
#pragma unroll
      for (int j = 0; j < 28; j++) {
        const uint32_t bw = b1s[j * 4 + (lane & 3)];
        const float2 ca = csa[j * 4 + (lane & 3)], cb = csa[112 + j * 4 + (lane & 3)];
        const float c0 = ca.x + cb.x, c1 = ca.y + cb.y;
        const float a0 = acc[4 * j], a1 = acc[4 * j + 1], a2 = acc[4 * j + 2], a3 = acc[4 * j + 3];
        const uint32_t p0 = hadd2_bf16(pack_bf16(fmaf(-st0.x, c0, a0) * st0.y, fmaf(-st0.x, c1, a1) * st0.y), bw);
        const uint32_t p1 = hadd2_bf16(pack_bf16(fmaf(-st1.x, c0, a2) * st1.y, fmaf(-st1.x, c1, a3) * st1.y), bw);
        ha[2 * j] = pack_bf16(gelu_tanh(bflo(p0)), gelu_tanh(bfhi(p0)));
        ha[2 * j + 1] = pack_bf16(gelu_tanh(bflo(p1)), gelu_tanh(bfhi(p1)));
      }
    }
    if (threadIdx.x == 0) TS(4);
#pragma unroll 1
    for (int q = 0; q < NJOB; q++) {
      float acc[64];
      const uint32_t jb = sb + (q == 0 || q == 3 ? SM_X : (q == 1 ? SM_X + 65536 : SM_RING));
#pragma unroll
      for (int h = 0; h < 2; h++) {
        mbar_wait(bar_full2 + 8 * (2 * q + h), 0);
        wgmma_fence();
#pragma unroll
        for (int kk = 0; kk < 7; kk++) {
          const int kb = h * 7 + kk;
          wgmma_n128_rs(acc, ha[4 * kb], ha[4 * kb + 1], ha[4 * kb + 2], ha[4 * kb + 3],
                        make_desc(jb + h * W2_HALF + kk * 2048, 14336, 1024, 1), kb > 0);
        }
        wgmma_commit();
      }
      if (q > 0 && lane == 0) {
        __threadfence();
        atomicAdd(&g_flag[(rt * NJOB + q - 1) * 8 + warp], 1u);
      }
      wgmma_wait<0>();
      if (q == 0) {
        __syncwarp();
        if (lane == 0) {
          __threadfence_block();
          if (atomicAdd(&relcnt[4], 1u) == 7u) { __threadfence_block(); load_w2(3, sb + SM_X); }
        }
      }
      uint4* dstp = g_part + ((((size_t)rt * NJOB + q) * 8 + warp) * 8 + sp) * 256 + lane;
#pragma unroll
      for (int i = 0; i < 8; i++) {
        uint4 o;
        o.x = pack_bf16(acc[8 * i + 0], acc[8 * i + 1]);
        o.y = pack_bf16(acc[8 * i + 2], acc[8 * i + 3]);
        o.z = pack_bf16(acc[8 * i + 4], acc[8 * i + 5]);
        o.w = pack_bf16(acc[8 * i + 6], acc[8 * i + 7]);
        dstp[i * 32] = o;
      }
      __syncwarp();
      if (threadIdx.x == 0) TS(5 + q);
    }
    if (lane == 0) {
      __threadfence();
      atomicAdd(&g_flag[(rt * NJOB + NJOB - 1) * 8 + warp], 1u);
    }
    {
      mbar_wait(bar_tile, 0);
      if (threadIdx.x == 0) TS(17);
      const float y256 = __ldcg(&g_spec[(size_t)256 * S_ + blockIdx.x * 16 + (threadIdx.x & 15)]).x;
      fft_pre(tile, y256, threadIdx.x, 1);
      tile_fft256(tile, threadIdx.x, 1);
      const int r = threadIdx.x & 15, q = threadIdx.x >> 4;
      float2 v[16];
#pragma unroll
      for (int i = 0; i < 16; i++) v[i] = *tile_at(tile, q + 16 * i, r);
      named_bar(1, 256);
      uint32_t* sw = reinterpret_cast<uint32_t*>(tile) + r * SPITCH;
#pragma unroll
      for (int i = 0; i < 16; i++) sw[q + 16 * i] = pack_bf16(v[i].x, -v[i].y);
      named_bar(1, 256);
      if (threadIdx.x == 0) TS(16);
    }
    {
      const int row0 = blockIdx.x * 16;
      const int g = lane >> 2, qd = lane & 3;
      const uint32_t* stile = reinterpret_cast<const uint32_t*>(smem + SM_FFT);
#pragma unroll 1
      for (int q0 = 0; q0 < NJOB; q0 += 2) {
        uint32_t bw[2][2], xw[2][4];
#pragma unroll
        for (int qq = 0; qq < 2; qq++)
#pragma unroll
          for (int c = 0; c < 4; c++) {
            const int col = (q0 + qq) * 128 + 8 * (2 * warp + (c >> 1)) + 2 * qd;
            if (!(c & 1)) bw[qq][c >> 1] = __ldg(reinterpret_cast<const uint32_t*>(b2 + col));
            xw[qq][c] = __ldg(reinterpret_cast<const uint32_t*>(x + (size_t)(row0 + g + 8 * (c & 1)) * D_ + col));
          }
        if (lane < 2) {
          const unsigned* fl = &g_flag[(rt * NJOB + q0 + lane) * 8 + sp];
          int it = 0;
          while (ld_acquire(fl) < 8u) {
            if (++it > (1 << 22)) __trap();
          }
        }
        __syncwarp();
        uint4 v[2][8];
#pragma unroll
        for (int qq = 0; qq < 2; qq++) {
          const uint4* src = g_part + (((size_t)rt * NJOB + q0 + qq) * 8 + sp) * 8 * 256 + warp * 32 + lane;
#pragma unroll
          for (int s = 0; s < 8; s++) v[qq][s] = __ldcg(src + s * 256);
        }
#pragma unroll
        for (int qq = 0; qq < 2; qq++) {
          float o[8];
#pragma unroll
          for (int c = 0; c < 8; c++) o[c] = 0.f;
#pragma unroll
          for (int s = 0; s < 8; s++) {
            o[0] += bflo(v[qq][s].x); o[1] += bfhi(v[qq][s].x); o[2] += bflo(v[qq][s].y); o[3] += bfhi(v[qq][s].y);
            o[4] += bflo(v[qq][s].z); o[5] += bfhi(v[qq][s].z); o[6] += bflo(v[qq][s].w); o[7] += bfhi(v[qq][s].w);
          }
#pragma unroll
          for (int c = 0; c < 4; c++) {
            const int row = g + 8 * (c & 1);
            const int col = (q0 + qq) * 128 + 8 * (2 * warp + (c >> 1)) + 2 * qd;
            const uint32_t sw = stile[row * SPITCH + (col >> 1)];
            const uint32_t p = hadd2_bf16(pack_bf16(o[2 * c], o[2 * c + 1]), bw[qq][c >> 1]);
            float r[2];
#pragma unroll
            for (int e = 0; e < 2; e++) {
              const float o2 = e ? bfhi(p) : bflo(p);
              const float gg = bf16r(__fdividef(o2, 1.0f + __expf(-o2)));
              const float sg = bf16r((e ? bfhi(sw) : bflo(sw)) * gg);
              r[e] = (e ? bfhi(xw[qq][c]) : bflo(xw[qq][c])) + sg;
            }
            *reinterpret_cast<uint32_t*>(out + (size_t)(row0 + row) * D_ + col) = pack_bf16(r[0], r[1]);
          }
        }
        if (threadIdx.x == 0) TS(20 + (q0 >> 1));
      }
      named_bar(1, 256);
      if (threadIdx.x < NJOB) g_flag[(rt * NJOB + threadIdx.x) * 8 + sp] = 0u;
    }
  }
}

typedef CUresult (*EncodeFn)(CUtensorMap*, CUtensorMapDataType, cuuint32_t, void*, const cuuint64_t*, const cuuint64_t*,
                             const cuuint32_t*, const cuuint32_t*, CUtensorMapInterleave, CUtensorMapSwizzle,
                             CUtensorMapL2promotion, CUtensorMapFloatOOBfill);

}

extern "C" void kernel_launch(void* const* d_in, const int* in_sizes, int n_in, void* d_out, int out_size) {
  const __nv_bfloat16* x = (const __nv_bfloat16*)d_in[0];
  const __nv_bfloat16* wr = (const __nv_bfloat16*)d_in[1];
  const __nv_bfloat16* wi = (const __nv_bfloat16*)d_in[2];
  const __nv_bfloat16* w1 = (const __nv_bfloat16*)d_in[4];
  const __nv_bfloat16* b1 = (const __nv_bfloat16*)d_in[5];
  const __nv_bfloat16* w2 = (const __nv_bfloat16*)d_in[6];
  const __nv_bfloat16* b2 = (const __nv_bfloat16*)d_in[7];
  __nv_bfloat16* out = (__nv_bfloat16*)d_out;

  static EncodeFn enc = nullptr;
  static void* p_spec = nullptr;
  static void* p_wt = nullptr;
  if (!enc) {
    void* fn = nullptr;
    cudaDriverEntryPointQueryResult qr;
    cudaGetDriverEntryPoint("cuTensorMapEncodeTiled", &fn, cudaEnableDefault, &qr);
    enc = (EncodeFn)fn;
    cudaFuncSetAttribute(k_mega, cudaFuncAttributeMaxDynamicSharedMemorySize, SM_TOTAL);
    cudaGetSymbolAddress(&p_spec, g_spec);
    cudaGetSymbolAddress(&p_wt, g_wt);
  }
  Maps m;
  const cuuint32_t es[3] = {1, 1, 1};
  {
    cuuint64_t dims[2] = {(cuuint64_t)D_, (cuuint64_t)S_};
    cuuint64_t strides[1] = {(cuuint64_t)D_ * 2};
    cuuint32_t box[2] = {64, 128};
    enc(&m.x, CU_TENSOR_MAP_DATA_TYPE_BFLOAT16, 2, (void*)x, dims, strides, box, es, CU_TENSOR_MAP_INTERLEAVE_NONE,
        CU_TENSOR_MAP_SWIZZLE_128B, CU_TENSOR_MAP_L2_PROMOTION_L2_128B, CU_TENSOR_MAP_FLOAT_OOB_FILL_NONE);
  }
  {
    cuuint64_t dims[3] = {32, 512, 56};
    cuuint64_t strides[2] = {(cuuint64_t)F_ * 2, 64};
    cuuint32_t box[3] = {32, 32, 7};
    enc(&m.w1, CU_TENSOR_MAP_DATA_TYPE_BFLOAT16, 3, (void*)w1, dims, strides, box, es, CU_TENSOR_MAP_INTERLEAVE_NONE,
        CU_TENSOR_MAP_SWIZZLE_64B, CU_TENSOR_MAP_L2_PROMOTION_L2_128B, CU_TENSOR_MAP_FLOAT_OOB_FILL_NONE);
  }
  {
    cuuint64_t dims[3] = {64, (cuuint64_t)F_, 8};
    cuuint64_t strides[2] = {(cuuint64_t)D_ * 2, 128};
    cuuint32_t box[3] = {64, 112, 2};
    enc(&m.w2, CU_TENSOR_MAP_DATA_TYPE_BFLOAT16, 3, (void*)w2, dims, strides, box, es, CU_TENSOR_MAP_INTERLEAVE_NONE,
        CU_TENSOR_MAP_SWIZZLE_128B, CU_TENSOR_MAP_L2_PROMOTION_L2_128B, CU_TENSOR_MAP_FLOAT_OOB_FILL_NONE);
  }
  {
    cuuint64_t dims[2] = {(cuuint64_t)S_, 256};
    cuuint64_t strides[1] = {(cuuint64_t)S_ * 8};
    cuuint32_t box[2] = {16, 256};
    enc(&m.spec, CU_TENSOR_MAP_DATA_TYPE_FLOAT64, 2, p_spec, dims, strides, box, es, CU_TENSOR_MAP_INTERLEAVE_NONE,
        CU_TENSOR_MAP_SWIZZLE_128B, CU_TENSOR_MAP_L2_PROMOTION_NONE, CU_TENSOR_MAP_FLOAT_OOB_FILL_NONE);
  }
  {
    cuuint64_t dims[2] = {(cuuint64_t)S_, 257};
    cuuint64_t strides[1] = {(cuuint64_t)S_ * 4};
    cuuint32_t box[2] = {16, 32};
    enc(&m.wt, CU_TENSOR_MAP_DATA_TYPE_UINT32, 2, p_wt, dims, strides, box, es, CU_TENSOR_MAP_INTERLEAVE_NONE,
        CU_TENSOR_MAP_SWIZZLE_64B, CU_TENSOR_MAP_L2_PROMOTION_NONE, CU_TENSOR_MAP_FLOAT_OOB_FILL_NONE);
  }
  k_mega<<<129, NTHREADS, SM_TOTAL>>>(x, wr, wi, b1, b2, out, m);
}
```

```cpp
#include <cuda_runtime.h>
#include <cuda_bf16.h>
#include <cuda.h>
#include <stdint.h>

namespace {

constexpr int S_ = 2048, D_ = 512, F_ = 1792, DF_ = 257;
constexpr int FC = 224;
constexpr int NJOB = 4;

__device__ __align__(1024) float2 g_spec[257 * 2048];
__device__ __align__(1024) uint32_t g_wt[257 * 2048];
__device__ uint4 g_part[16 * NJOB * 8 * 8 * 256];
__device__ float2 g_stats[2048];
__device__ unsigned g_bar[2];
__device__ unsigned g_flag[16 * NJOB * 8];
#define TS(i)

__device__ __forceinline__ uint32_t smem_u32(const void* p) { return (uint32_t)__cvta_generic_to_shared(p); }
__device__ __forceinline__ float bf16r(float x) { return __bfloat162float(__float2bfloat16_rn(x)); }
__device__ __forceinline__ float bflo(uint32_t w) { return __uint_as_float(w << 16); }
__device__ __forceinline__ float bfhi(uint32_t w) { return __uint_as_float(w & 0xffff0000u); }
__device__ __forceinline__ uint32_t pack_bf16(float lo, float hi) {
  uint32_t r;
  asm("cvt.rn.bf16x2.f32 %0, %1, %2;" : "=r"(r) : "f"(hi), "f"(lo));
  return r;
}
__device__ __forceinline__ uint32_t hadd2_bf16(uint32_t a, uint32_t b) {
  uint32_t r;
  asm("add.rn.bf16x2 %0, %1, %2;" : "=r"(r) : "r"(a), "r"(b));
  return r;
}
__device__ __forceinline__ void named_bar(int id, int n) { asm volatile("bar.sync %0, %1;" ::"r"(id), "r"(n) : "memory"); }
__device__ __forceinline__ void fence_async() { asm volatile("fence.proxy.async;" ::: "memory"); }

__device__ __forceinline__ void mbar_init(uint32_t bar, int cnt) { asm volatile("mbarrier.init.shared::cta.b64 [%0], %1;" ::"r"(bar), "r"(cnt) : "memory"); }
__device__ __forceinline__ void mbar_expect_tx(uint32_t bar, uint32_t bytes) { asm volatile("mbarrier.arrive.expect_tx.shared::cta.b64 _, [%0], %1;" ::"r"(bar), "r"(bytes) : "memory"); }
__device__ __forceinline__ void mbar_arrive(uint32_t bar) { asm volatile("mbarrier.arrive.shared::cta.b64 _, [%0];" ::"r"(bar) : "memory"); }
__device__ __forceinline__ bool mbar_try(uint32_t bar, uint32_t parity) {
  uint32_t ok;
  asm volatile("{\n.reg .pred p;\nmbarrier.try_wait.parity.shared::cta.b64 p, [%1], %2, %3;\nselp.u32 %0, 1, 0, p;\n}\n" : "=r"(ok) : "r"(bar), "r"(parity), "r"(20000u) : "memory");
  return ok != 0;
}
__device__ __forceinline__ void mbar_wait(uint32_t bar, uint32_t parity) {
  int it = 0;
  while (!mbar_try(bar, parity)) {
    if (++it > (1 << 17)) __trap();
  }
}
__device__ __forceinline__ void tma_load_3d(uint32_t dst, const CUtensorMap* map, int c0, int c1, int c2, uint32_t bar) {
  asm volatile("cp.async.bulk.tensor.3d.shared::cluster.global.mbarrier::complete_tx::bytes [%0], [%1, {%3, %4, %5}], [%2];"
               ::"r"(dst), "l"((uint64_t)map), "r"(bar), "r"(c0), "r"(c1), "r"(c2) : "memory");
}
__device__ __forceinline__ void tma_load_2d(uint32_t dst, const CUtensorMap* map, int c0, int c1, uint32_t bar) {
  asm volatile("cp.async.bulk.tensor.2d.shared::cluster.global.mbarrier::complete_tx::bytes [%0], [%1, {%3, %4}], [%2];"
               ::"r"(dst), "l"((uint64_t)map), "r"(bar), "r"(c0), "r"(c1) : "memory");
}
__device__ __forceinline__ void tma_store_2d(const CUtensorMap* map, int c0, int c1, uint32_t src) {
  asm volatile("cp.async.bulk.tensor.2d.global.shared::cta.bulk_group [%0, {%2, %3}], [%1];"
               ::"l"((uint64_t)map), "r"(src), "r"(c0), "r"(c1) : "memory");
}
__device__ __forceinline__ void tma_store_commit_wait() {
  asm volatile("cp.async.bulk.commit_group;" ::: "memory");
  asm volatile("cp.async.bulk.wait_group 0;" ::: "memory");
}
__device__ __forceinline__ void wgmma_fence() { asm volatile("wgmma.fence.sync.aligned;" ::: "memory"); }
__device__ __forceinline__ void wgmma_commit() { asm volatile("wgmma.commit_group.sync.aligned;" ::: "memory"); }
template <int N> __device__ __forceinline__ void wgmma_wait() { asm volatile("wgmma.wait_group.sync.aligned %0;" ::"n"(N) : "memory"); }
__device__ __forceinline__ uint64_t make_desc(uint32_t addr, uint32_t lbo_bytes, uint32_t sbo_bytes, uint32_t swz) {
  uint64_t d = 0;
  d |= (uint64_t)((addr & 0x3FFFF) >> 4);
  d |= (uint64_t)((lbo_bytes & 0x3FFFF) >> 4) << 16;
  d |= (uint64_t)((sbo_bytes & 0x3FFFF) >> 4) << 32;
  d |= (uint64_t)swz << 62;
  return d;
}
__device__ __forceinline__ unsigned ld_acquire(const unsigned* p) {
  unsigned v;
  asm volatile("ld.acquire.gpu.global.u32 %0, [%1];" : "=r"(v) : "l"(p) : "memory");
  return v;
}

__device__ __forceinline__ void wgmma_n224_ss(float (&d)[112], uint64_t da, uint64_t db, int scale_d) {
  asm volatile("{\n.reg .pred p;\nsetp.ne.b32 p, %114, 0;\n"
    "wgmma.mma_async.sync.aligned.m64n224k16.f32.bf16.bf16 {%0, %1, %2, %3, %4, %5, %6, %7, %8, %9, %10, %11, %12, %13, %14, %15, %16, %17, %18, %19, %20, %21, %22, %23, %24, %25, %26, %27, %28, %29, %30, %31, %32, %33, %34, %35, %36, %37, %38, %39, %40, %41, %42, %43, %44, %45, %46, %47, %48, %49, %50, %51, %52, %53, %54, %55, %56, %57, %58, %59, %60, %61, %62, %63, %64, %65, %66, %67, %68, %69, %70, %71, %72, %73, %74, %75, %76, %77, %78, %79, %80, %81, %82, %83, %84, %85, %86, %87, %88, %89, %90, %91, %92, %93, %94, %95, %96, %97, %98, %99, %100, %101, %102, %103, %104, %105, %106, %107, %108, %109, %110, %111}, %112, %113, p, 1, 1, 0, 1;\n}\n"
    : "+f"(d[0]), "+f"(d[1]), "+f"(d[2]), "+f"(d[3]), "+f"(d[4]), "+f"(d[5]), "+f"(d[6]), "+f"(d[7]), "+f"(d[8]), "+f"(d[9]), "+f"(d[10]), "+f"(d[11]), "+f"(d[12]), "+f"(d[13]), "+f"(d[14]), "+f"(d[15]), "+f"(d[16]), "+f"(d[17]), "+f"(d[18]), "+f"(d[19]), "+f"(d[20]), "+f"(d[21]), "+f"(d[22]), "+f"(d[23]), "+f"(d[24]), "+f"(d[25]), "+f"(d[26]), "+f"(d[27]), "+f"(d[28]), "+f"(d[29]), "+f"(d[30]), "+f"(d[31]), "+f"(d[32]), "+f"(d[33]), "+f"(d[34]), "+f"(d[35]), "+f"(d[36]), "+f"(d[37]), "+f"(d[38]), "+f"(d[39]), "+f"(d[40]), "+f"(d[41]), "+f"(d[42]), "+f"(d[43]), "+f"(d[44]), "+f"(d[45]), "+f"(d[46]), "+f"(d[47]), "+f"(d[48]), "+f"(d[49]), "+f"(d[50]), "+f"(d[51]), "+f"(d[52]), "+f"(d[53]), "+f"(d[54]), "+f"(d[55]), "+f"(d[56]), "+f"(d[57]), "+f"(d[58]), "+f"(d[59]), "+f"(d[60]), "+f"(d[61]), "+f"(d[62]), "+f"(d[63]), "+f"(d[64]), "+f"(d[65]), "+f"(d[66]), "+f"(d[67]), "+f"(d[68]), "+f"(d[69]), "+f"(d[70]), "+f"(d[71]), "+f"(d[72]), "+f"(d[73]), "+f"(d[74]), "+f"(d[75]), "+f"(d[76]), "+f"(d[77]), "+f"(d[78]), "+f"(d[79]), "+f"(d[80]), "+f"(d[81]), "+f"(d[82]), "+f"(d[83]), "+f"(d[84]), "+f"(d[85]), "+f"(d[86]), "+f"(d[87]), "+f"(d[88]), "+f"(d[89]), "+f"(d[90]), "+f"(d[91]), "+f"(d[92]), "+f"(d[93]), "+f"(d[94]), "+f"(d[95]), "+f"(d[96]), "+f"(d[97]), "+f"(d[98]), "+f"(d[99]), "+f"(d[100]), "+f"(d[101]), "+f"(d[102]), "+f"(d[103]), "+f"(d[104]), "+f"(d[105]), "+f"(d[106]), "+f"(d[107]), "+f"(d[108]), "+f"(d[109]), "+f"(d[110]), "+f"(d[111])
    : "l"(da), "l"(db), "r"(scale_d));
}
__device__ __forceinline__ void wgmma_n128_ss(float (&d)[64], uint64_t da, uint64_t db, int scale_d) {
  asm volatile("{\n.reg .pred p;\nsetp.ne.b32 p, %66, 0;\n"
    "wgmma.mma_async.sync.aligned.m64n128k16.f32.bf16.bf16 {%0, %1, %2, %3, %4, %5, %6, %7, %8, %9, %10, %11, %12, %13, %14, %15, %16, %17, %18, %19, %20, %21, %22, %23, %24, %25, %26, %27, %28, %29, %30, %31, %32, %33, %34, %35, %36, %37, %38, %39, %40, %41, %42, %43, %44, %45, %46, %47, %48, %49, %50, %51, %52, %53, %54, %55, %56, %57, %58, %59, %60, %61, %62, %63}, %64, %65, p, 1, 1, 0, 1;\n}\n"
    : "+f"(d[0]), "+f"(d[1]), "+f"(d[2]), "+f"(d[3]), "+f"(d[4]), "+f"(d[5]), "+f"(d[6]), "+f"(d[7]), "+f"(d[8]), "+f"(d[9]), "+f"(d[10]), "+f"(d[11]), "+f"(d[12]), "+f"(d[13]), "+f"(d[14]), "+f"(d[15]), "+f"(d[16]), "+f"(d[17]), "+f"(d[18]), "+f"(d[19]), "+f"(d[20]), "+f"(d[21]), "+f"(d[22]), "+f"(d[23]), "+f"(d[24]), "+f"(d[25]), "+f"(d[26]), "+f"(d[27]), "+f"(d[28]), "+f"(d[29]), "+f"(d[30]), "+f"(d[31]), "+f"(d[32]), "+f"(d[33]), "+f"(d[34]), "+f"(d[35]), "+f"(d[36]), "+f"(d[37]), "+f"(d[38]), "+f"(d[39]), "+f"(d[40]), "+f"(d[41]), "+f"(d[42]), "+f"(d[43]), "+f"(d[44]), "+f"(d[45]), "+f"(d[46]), "+f"(d[47]), "+f"(d[48]), "+f"(d[49]), "+f"(d[50]), "+f"(d[51]), "+f"(d[52]), "+f"(d[53]), "+f"(d[54]), "+f"(d[55]), "+f"(d[56]), "+f"(d[57]), "+f"(d[58]), "+f"(d[59]), "+f"(d[60]), "+f"(d[61]), "+f"(d[62]), "+f"(d[63])
    : "l"(da), "l"(db), "r"(scale_d));
}
__device__ __forceinline__ void wgmma_n96_ss(float (&d)[48], uint64_t da, uint64_t db, int scale_d) {
  asm volatile("{\n.reg .pred p;\nsetp.ne.b32 p, %50, 0;\n"
    "wgmma.mma_async.sync.aligned.m64n96k16.f32.bf16.bf16 {%0, %1, %2, %3, %4, %5, %6, %7, %8, %9, %10, %11, %12, %13, %14, %15, %16, %17, %18, %19, %20, %21, %22, %23, %24, %25, %26, %27, %28, %29, %30, %31, %32, %33, %34, %35, %36, %37, %38, %39, %40, %41, %42, %43, %44, %45, %46, %47}, %48, %49, p, 1, 1, 0, 1;\n}\n"
    : "+f"(d[0]), "+f"(d[1]), "+f"(d[2]), "+f"(d[3]), "+f"(d[4]), "+f"(d[5]), "+f"(d[6]), "+f"(d[7]), "+f"(d[8]), "+f"(d[9]), "+f"(d[10]), "+f"(d[11]), "+f"(d[12]), "+f"(d[13]), "+f"(d[14]), "+f"(d[15]), "+f"(d[16]), "+f"(d[17]), "+f"(d[18]), "+f"(d[19]), "+f"(d[20]), "+f"(d[21]), "+f"(d[22]), "+f"(d[23]), "+f"(d[24]), "+f"(d[25]), "+f"(d[26]), "+f"(d[27]), "+f"(d[28]), "+f"(d[29]), "+f"(d[30]), "+f"(d[31]), "+f"(d[32]), "+f"(d[33]), "+f"(d[34]), "+f"(d[35]), "+f"(d[36]), "+f"(d[37]), "+f"(d[38]), "+f"(d[39]), "+f"(d[40]), "+f"(d[41]), "+f"(d[42]), "+f"(d[43]), "+f"(d[44]), "+f"(d[45]), "+f"(d[46]), "+f"(d[47])
    : "l"(da), "l"(db), "r"(scale_d));
}
__device__ __forceinline__ void wgmma_n128_rs(float (&d)[64], uint32_t a0, uint32_t a1, uint32_t a2, uint32_t a3, uint64_t db, int scale_d) {
  asm volatile("{\n.reg .pred p;\nsetp.ne.b32 p, %69, 0;\n"
    "wgmma.mma_async.sync.aligned.m64n128k16.f32.bf16.bf16 {%0, %1, %2, %3, %4, %5, %6, %7, %8, %9, %10, %11, %12, %13, %14, %15, %16, %17, %18, %19, %20, %21, %22, %23, %24, %25, %26, %27, %28, %29, %30, %31, %32, %33, %34, %35, %36, %37, %38, %39, %40, %41, %42, %43, %44, %45, %46, %47, %48, %49, %50, %51, %52, %53, %54, %55, %56, %57, %58, %59, %60, %61, %62, %63}, {%64, %65, %66, %67}, %68, p, 1, 1, 1;\n}\n"
    : "+f"(d[0]), "+f"(d[1]), "+f"(d[2]), "+f"(d[3]), "+f"(d[4]), "+f"(d[5]), "+f"(d[6]), "+f"(d[7]), "+f"(d[8]), "+f"(d[9]), "+f"(d[10]), "+f"(d[11]), "+f"(d[12]), "+f"(d[13]), "+f"(d[14]), "+f"(d[15]), "+f"(d[16]), "+f"(d[17]), "+f"(d[18]), "+f"(d[19]), "+f"(d[20]), "+f"(d[21]), "+f"(d[22]), "+f"(d[23]), "+f"(d[24]), "+f"(d[25]), "+f"(d[26]), "+f"(d[27]), "+f"(d[28]), "+f"(d[29]), "+f"(d[30]), "+f"(d[31]), "+f"(d[32]), "+f"(d[33]), "+f"(d[34]), "+f"(d[35]), "+f"(d[36]), "+f"(d[37]), "+f"(d[38]), "+f"(d[39]), "+f"(d[40]), "+f"(d[41]), "+f"(d[42]), "+f"(d[43]), "+f"(d[44]), "+f"(d[45]), "+f"(d[46]), "+f"(d[47]), "+f"(d[48]), "+f"(d[49]), "+f"(d[50]), "+f"(d[51]), "+f"(d[52]), "+f"(d[53]), "+f"(d[54]), "+f"(d[55]), "+f"(d[56]), "+f"(d[57]), "+f"(d[58]), "+f"(d[59]), "+f"(d[60]), "+f"(d[61]), "+f"(d[62]), "+f"(d[63])
    : "r"(a0), "r"(a1), "r"(a2), "r"(a3), "l"(db), "r"(scale_d));
}

__device__ __forceinline__ float2 cadd(float2 a, float2 b) { return make_float2(a.x + b.x, a.y + b.y); }
__device__ __forceinline__ float2 csub(float2 a, float2 b) { return make_float2(a.x - b.x, a.y - b.y); }
__device__ __forceinline__ float2 cmul(float2 a, float2 b) { return make_float2(a.x * b.x - a.y * b.y, a.x * b.y + a.y * b.x); }
__device__ __forceinline__ float2 cconj(float2 a) { return make_float2(a.x, -a.y); }

template <int DIR> __device__ __forceinline__ void dft4(float2& a0, float2& a1, float2& a2, float2& a3) {
  float2 t0 = cadd(a0, a2), t1 = csub(a0, a2), t2 = cadd(a1, a3), t3 = csub(a1, a3);
  float2 t3r = DIR < 0 ? make_float2(t3.y, -t3.x) : make_float2(-t3.y, t3.x);
  a0 = cadd(t0, t2); a2 = csub(t0, t2); a1 = cadd(t1, t3r); a3 = csub(t1, t3r);
}
template <int DIR> __device__ __forceinline__ float2 mulw(float2 v, float c, float s) {
  return DIR < 0 ? make_float2(v.x * c + v.y * s, v.y * c - v.x * s) : make_float2(v.x * c - v.y * s, v.y * c + v.x * s);
}
template <int DIR> __device__ __forceinline__ float2 muli(float2 v) {
  return DIR < 0 ? make_float2(v.y, -v.x) : make_float2(-v.y, v.x);
}
#define O16(k) (4 * ((k) & 3) + ((k) >> 2))
#define O8(k) (2 * ((k) & 3) + ((k) >> 2))
template <int DIR> __device__ __forceinline__ void dft16(float2 (&v)[16]) {
  constexpr float C1 = 0.92387953251128674f, S1 = 0.38268343236508977f, R = 0.70710678118654752f;
#pragma unroll
  for (int n2 = 0; n2 < 4; n2++) dft4<DIR>(v[n2], v[4 + n2], v[8 + n2], v[12 + n2]);
  v[5] = mulw<DIR>(v[5], C1, S1);
  v[6] = mulw<DIR>(v[6], R, R);
  v[7] = mulw<DIR>(v[7], S1, C1);
  v[9] = mulw<DIR>(v[9], R, R);
  v[10] = muli<DIR>(v[10]);
  v[11] = mulw<DIR>(v[11], -R, R);
  v[13] = mulw<DIR>(v[13], S1, C1);
  v[14] = mulw<DIR>(v[14], -R, R);
  v[15] = mulw<DIR>(v[15], -C1, -S1);
#pragma unroll
  for (int k1 = 0; k1 < 4; k1++) dft4<DIR>(v[4 * k1], v[4 * k1 + 1], v[4 * k1 + 2], v[4 * k1 + 3]);
}
template <int DIR> __device__ __forceinline__ void dft8(float2 (&v)[8]) {
  constexpr float R = 0.70710678118654752f;
  dft4<DIR>(v[0], v[2], v[4], v[6]);
  dft4<DIR>(v[1], v[3], v[5], v[7]);
  v[3] = mulw<DIR>(v[3], R, R);
  v[5] = muli<DIR>(v[5]);
  v[7] = mulw<DIR>(v[7], -R, R);
#pragma unroll
  for (int k1 = 0; k1 < 4; k1++) {
    float2 a = v[2 * k1], b = v[2 * k1 + 1];
    v[2 * k1] = cadd(a, b); v[2 * k1 + 1] = csub(a, b);
  }
}
template <int N> __device__ __forceinline__ float2 twcs(int m) {
  m &= (N - 1);
  if (m >= N / 2) m -= N;
  float s, c;
  __sincosf((float)m * (6.283185307179586f / N), &s, &c);
  return make_float2(c, s);
}

__device__ __forceinline__ void twiddle16(float2 (&v)[16], int m) {
  const float2 w1 = twcs<2048>(m);
  float2 w = w1;
#pragma unroll
  for (int k = 1; k < 16; k++) {
    v[O16(k)] = mulw<-1>(v[O16(k)], w.x, w.y);
    if (k < 15) w = cmul(w, w1);
  }
}
__device__ __forceinline__ float2* tile_at(uint8_t* tile, int k, int r) {
  return reinterpret_cast<float2*>(tile + k * 128 + ((((r >> 1) ^ k) & 7) << 4) + (r & 1) * 8);
}
constexpr int SPITCH = 260;

constexpr int STEP = 45056;
constexpr int W1_STAGE = 14336;
constexpr int SM_FFT = 184 * 1024;
constexpr int SM_WT = SM_FFT + 32768;
constexpr int SM_B1 = SM_WT + 8192;
constexpr int SM_CS = SM_B1 + 512;
constexpr int SM_BAR = SM_CS + 2 * FC * 4;
constexpr int SM_TOTAL = SM_BAR + 256;
constexpr int NTHREADS = 384;

__device__ __forceinline__ float gelu2(float x) {
  float u = x * (0.7978845608028654f + 0.035677408136300125f * x * x);
  float th;
  asm("tanh.approx.f32 %0, %1;" : "=f"(th) : "f"(u));
  return fmaf(x, th, x);
}
__device__ __forceinline__ unsigned grid_arrive(unsigned* cnt) {
  __threadfence();
  unsigned old = atomicAdd(cnt, 1u);
  return (old / 129u + 1u) * 129u;
}
__device__ __forceinline__ void grid_wait(const unsigned* cnt, unsigned target) {
  int it = 0;
  while ((int)(ld_acquire(cnt) - target) < 0) {
    if (++it > (1 << 22)) __trap();
  }
}
__device__ __forceinline__ uint32_t piece_off(int p) {
  if (p >= 12) p -= 12;
  const int s = (p * 11) >> 5;
  return (uint32_t)(s * STEP + (p - 3 * s) * W1_STAGE);
}

struct Maps { CUtensorMap x, w1, w2, spec, wt; };

__device__ __forceinline__ void load_step(uint32_t sb, const Maps& maps, int rt, int sp, int j) {
  const uint32_t dst = sb + (j & 3) * STEP, bar = sb + SM_BAR + 8 * (j & 3);
  mbar_expect_tx(bar, STEP);
  tma_load_2d(dst, &maps.x, j * 64, rt * 128, bar);
  tma_load_3d(dst + 16384, &maps.w1, 0, j * 64, sp * 7, bar);
  tma_load_3d(dst + 16384 + W1_STAGE, &maps.w1, 0, j * 64 + 32, sp * 7, bar);
}
__device__ __forceinline__ void load_piece(uint32_t sb, const Maps& maps, int sp, int p) {
  const uint32_t bar = sb + SM_BAR + 64 + 8 * (p >> 1);
  mbar_expect_tx(bar, W1_STAGE);
  tma_load_2d(sb + piece_off(p), &maps.w2, (p >> 2) * 128 + (p & 1) * 64, sp * FC + ((p >> 1) & 1) * 112, bar);
}

__device__ __forceinline__ void gemm_part(uint8_t* smem, const Maps& maps, int rt, int sp) {
  const uint32_t sb = smem_u32(smem);
  const int tid = threadIdx.x, warp = tid >> 5, lane = tid & 31, wg = warp >> 2, tt = tid & 127;
  const uint32_t bar_full1 = sb + SM_BAR, bar_full2 = sb + SM_BAR + 64;
  unsigned* relcnt = reinterpret_cast<unsigned*>(smem + SM_BAR + 128);
  const uint32_t bar_stats = sb + SM_BAR + 160, bar_g2 = sb + SM_BAR + 184;
  uint32_t ha[56];
      auto release = [&](int j) {
        __syncwarp();
        if (lane == 0) {
          __threadfence_block();
          if ((atomicAdd(&relcnt[j & 3], 1u) & 7u) == 7u) {
            __threadfence_block();
            if (j < 4) load_step(sb, maps, rt, sp, j + 4);
            else {
#pragma unroll 1
              for (int p = 3 * (j - 4); p < 3 * (j - 4) + 3; p++) load_piece(sb, maps, sp, p);
            }
          }
        }
      };
      {
        float acc[112];
#pragma unroll
        for (int i = 0; i < 112; i++) acc[i] = 0.f;
        float cs0 = 0.f, cs1 = 0.f;
        const uint32_t cs_base = 16384 + (uint32_t)(tt >> 4) * 2048 + (uint32_t)wg * 1024 + (uint32_t)(tt & 3) * 4;
        const uint32_t cs_c = (tt >> 2) & 3;
#pragma unroll 1
        for (int j = 0; j < 8; j++) {
          const uint32_t base = (j & 3) * STEP;
          mbar_wait(bar_full1 + 8 * (j & 3), j >> 2);
          if (tid == 0) TS(24 + j);
          wgmma_fence();
#pragma unroll
          for (int kk = 0; kk < 4; kk++)
            wgmma_n224_ss(acc, make_desc(sb + base + wg * 8192 + kk * 32, 16, 1024, 1),
                          make_desc(sb + base + 16384 + (kk >> 1) * W1_STAGE + (kk & 1) * 1024, 2048, 512, 2), 1);
          wgmma_commit();
          if (tt < 112) {
#pragma unroll 1
            for (int h = 0; h < 2; h++) {
              const uint8_t* st = smem + base + cs_base + h * W1_STAGE;
#pragma unroll
              for (int k = 0; k < 16; k++) {
                const uint32_t w = *reinterpret_cast<const uint32_t*>(st + k * 64 + ((cs_c ^ ((k >> 1) & 3)) << 4));
                cs0 += bflo(w); cs1 += bfhi(w);
              }
            }
          }
          if (j > 0) {
            wgmma_wait<1>();
            release(j - 1);
          }
        }
        if (tt < 112) *reinterpret_cast<float2*>(smem + SM_CS + wg * FC * 4 + tt * 8) = make_float2(cs0, cs1);
        wgmma_wait<0>();
        release(7);
        if (tid == 0) TS(2);
        named_bar(1, 256);
        if (tid < 112) {
          const float2* csa = reinterpret_cast<const float2*>(smem + SM_CS);
          const uint32_t bw = reinterpret_cast<const uint32_t*>(smem + SM_B1)[tid];
          reinterpret_cast<float4*>(smem + SM_WT)[tid] = make_float4(csa[tid].x + csa[112 + tid].x, csa[tid].y + csa[112 + tid].y, bflo(bw), bfhi(bw));
        }
        mbar_wait(bar_stats, 0);
        const int row = rt * 128 + warp * 16 + (lane >> 2);
        const float2 st0 = __ldcg(&g_stats[row]), st1 = __ldcg(&g_stats[row + 8]);
        named_bar(1, 256);
        if (tid == 0) TS(3);
        const float4* csb = reinterpret_cast<const float4*>(smem + SM_WT) + (lane & 3);
#pragma unroll
        for (int j = 0; j < 28; j++) {
          const float4 c = csb[j * 4];
          ha[2 * j] = pack_bf16(gelu2(fmaf(fmaf(-st0.x, c.x, acc[4 * j]), st0.y, c.z)), gelu2(fmaf(fmaf(-st0.x, c.y, acc[4 * j + 1]), st0.y, c.w)));
          ha[2 * j + 1] = pack_bf16(gelu2(fmaf(fmaf(-st1.x, c.x, acc[4 * j + 2]), st1.y, c.z)), gelu2(fmaf(fmaf(-st1.x, c.y, acc[4 * j + 3]), st1.y, c.w)));
        }
      }
      if (tid == 0) TS(4);
#pragma unroll 1
      for (int jq = 0; jq < NJOB; jq++) {
        float acc[64];
#pragma unroll
        for (int h = 0; h < 2; h++) {
          const uint32_t o0 = piece_off(4 * jq + 2 * h), o1 = piece_off(4 * jq + 2 * h + 1);
          mbar_wait(bar_full2 + 8 * (2 * jq + h), 0);
          wgmma_fence();
#pragma unroll
          for (int kk = 0; kk < 7; kk++) {
            const int kb = h * 7 + kk;
            wgmma_n128_rs(acc, ha[4 * kb], ha[4 * kb + 1], ha[4 * kb + 2], ha[4 * kb + 3],
                          make_desc(sb + o0 + kk * 2048, o1 - o0, 1024, 1), kb > 0);
          }
          wgmma_commit();
        }
        if (jq > 0 && lane == 0) {
          __threadfence();
          atomicAdd(&g_flag[(rt * NJOB + jq - 1) * 8 + warp], 1u);
        }
        wgmma_wait<0>();
        if (jq == 0) {
          __syncwarp();
          if (lane == 0) {
            __threadfence_block();
            if (atomicAdd(&relcnt[4], 1u) == 7u) {
              __threadfence_block();
#pragma unroll 1
              for (int p = 12; p < 16; p++) load_piece(sb, maps, sp, p);
            }
          }
        }
        uint4* dstp = g_part + ((((size_t)rt * NJOB + jq) * 8 + warp) * 8 + sp) * 256 + lane;
#pragma unroll
        for (int i = 0; i < 8; i++) {
          uint4 o;
          o.x = pack_bf16(acc[8 * i + 0], acc[8 * i + 1]);
          o.y = pack_bf16(acc[8 * i + 2], acc[8 * i + 3]);
          o.z = pack_bf16(acc[8 * i + 4], acc[8 * i + 5]);
          o.w = pack_bf16(acc[8 * i + 6], acc[8 * i + 7]);
          dstp[i * 32] = o;
        }
        __syncwarp();
        if (tid == 0) TS(5 + jq);
      }
      if (lane == 0) {
        mbar_arrive(bar_g2);
        __threadfence();
        atomicAdd(&g_flag[(rt * NJOB + NJOB - 1) * 8 + warp], 1u);
      }
}

__global__ void __launch_bounds__(NTHREADS, 1)
k_mega(const __nv_bfloat16* __restrict__ x, const __nv_bfloat16* __restrict__ wr, const __nv_bfloat16* __restrict__ wi,
       const __nv_bfloat16* __restrict__ b1, const __nv_bfloat16* __restrict__ b2, __nv_bfloat16* __restrict__ out,
       const __grid_constant__ Maps maps) {
  extern __shared__ __align__(1024) uint8_t smem[];
  const uint32_t sb = smem_u32(smem);
  const int rt = blockIdx.x >> 3, sp = blockIdx.x & 7;
  const int warp = threadIdx.x >> 5, lane = threadIdx.x & 31;
  const int s0 = blockIdx.x * 16;
  if (threadIdx.x == 0) TS(0);
  const uint32_t bar_full1 = sb + SM_BAR;
  const uint32_t bar_full2 = sb + SM_BAR + 64;
  unsigned* relcnt = reinterpret_cast<unsigned*>(smem + SM_BAR + 128);
  const uint32_t bar_stats = sb + SM_BAR + 160;
  const uint32_t bar_p1 = sb + SM_BAR + 168;
  const uint32_t bar_tile = sb + SM_BAR + 176;
  const uint32_t bar_g2 = sb + SM_BAR + 184;
  const uint32_t bar_g = sb + SM_BAR + 192;
  uint8_t* tile = smem + SM_FFT;

  if (threadIdx.x == 0) {
    for (int i = 0; i < 4; i++) mbar_init(bar_full1 + 8 * i, 1);
    for (int i = 0; i < 8; i++) mbar_init(bar_full2 + 8 * i, 2);
    mbar_init(bar_stats, 1); mbar_init(bar_p1, 256); mbar_init(bar_tile, 1); mbar_init(bar_g2, 8);
    for (int i = 0; i < 4; i++) mbar_init(bar_g + 8 * i, 1);
    for (int i = 0; i < 5; i++) relcnt[i] = 0;
    asm volatile("fence.mbarrier_init.release.cluster;" ::: "memory");
    if (blockIdx.x < 128) {
#pragma unroll 1
      for (int j = 0; j < 4; j++) load_step(sb, maps, rt, sp, j);
    }
  }
  __syncthreads();

  if (warp >= 8) {
    const int t = threadIdx.x & 127;
    const bool extra = blockIdx.x == 128;
    if (!extra) {
      const uint32_t stg = (uint32_t)(SM_WT + (warp - 8) * 2048);
      if (t < 16) {
        const size_t o = (size_t)(s0 + t) * DF_ + 256;
        g_wt[(size_t)256 * S_ + s0 + t] = (uint32_t)__ldg(reinterpret_cast<const unsigned short*>(wr) + o) |
                                          ((uint32_t)__ldg(reinterpret_cast<const unsigned short*>(wi) + o) << 16);
      }
#pragma unroll 1
      for (int rd = 0; rd < 2; rd++) {
        const unsigned short* pr = reinterpret_cast<const unsigned short*>(wr) + (size_t)s0 * DF_ + rd * 128 + t;
        const unsigned short* pi = reinterpret_cast<const unsigned short*>(wi) + (size_t)s0 * DF_ + rd * 128 + t;
        uint32_t wv[16];
#pragma unroll
        for (int u = 0; u < 16; u++) wv[u] = (uint32_t)__ldg(pr + u * DF_) | ((uint32_t)__ldg(pi + u * DF_) << 16);
        if (rd && lane == 0) asm volatile("cp.async.bulk.wait_group.read 0;" ::: "memory");
        __syncwarp();
#pragma unroll
        for (int c = 0; c < 4; c++)
          *reinterpret_cast<uint4*>(smem + stg + lane * 64 + ((c ^ ((lane >> 1) & 3)) << 4)) =
              make_uint4(wv[4 * c], wv[4 * c + 1], wv[4 * c + 2], wv[4 * c + 3]);
        fence_async();
        __syncwarp();
        if (lane == 0) {
          tma_store_2d(&maps.wt, s0, rd * 128 + (warp - 8) * 32, sb + stg);
          asm volatile("cp.async.bulk.commit_group;" ::: "memory");
        }
      }
      if (lane == 0) { asm volatile("cp.async.bulk.wait_group 0;" ::: "memory"); __threadfence(); }
    }
    named_bar(3, 128);
    if (t == 0) {
      TS(11);
      if (!extra) {
        mbar_wait(bar_p1, 0);
        tma_store_2d(&maps.spec, s0, 0, sb + SM_FFT);
        tma_store_commit_wait();
      }
      TS(12);
      const unsigned target = grid_arrive(&g_bar[0]);
      grid_wait(&g_bar[0], target);
      mbar_arrive(bar_stats);
    }
    named_bar(3, 128);
    if (t == 0) TS(13);
    {
      float2* buf = reinterpret_cast<float2*>(tile);
      const int k1 = t >> 3, m2 = t & 7;
      const int c0 = extra ? 256 : blockIdx.x * 2, nc = extra ? 1 : 2;
      float2 vn[16];
      uint32_t wn[16];
#pragma unroll 1
      for (int c = -1; c < nc; c++) {
        uint32_t wq[16];
        if (c >= 0) {
#pragma unroll
          for (int i = 0; i < 16; i++) { buf[128 * i + t] = vn[i]; wq[i] = wn[i]; }
        }
        if (c + 1 < nc) {
#pragma unroll
          for (int i = 0; i < 16; i++) {
            vn[i] = __ldcg(g_spec + (size_t)(c0 + c + 1) * S_ + 128 * i + t);
            wn[i] = __ldcg(g_wt + (size_t)(c0 + c + 1) * S_ + 128 * i + t);
          }
        }
        if (c < 0) continue;
#pragma unroll 1
        for (int it = 0; it < 2; it++) {
#pragma unroll 1
          for (int p = 0; p < 2; p++) {
            const float2* in = buf + (p ? k1 * 136 + m2 : t);
            const int is = p ? 8 : 128;
            float2 v[16];
#pragma unroll
            for (int i = 0; i < 16; i++) v[i] = in[i * is];
            dft16<-1>(v);
            twiddle16(v, p ? 16 * m2 : t);
            named_bar(3, 128);
            float2* o = buf + (p ? k1 * 9 + m2 : t);
            const int os = p ? 144 : 136;
#pragma unroll
            for (int kk = 0; kk < 16; kk++) o[kk * os] = v[O16(kk)];
            named_bar(3, 128);
          }
          float2 e[2][8];
#pragma unroll
          for (int m = 0; m < 8; m++) { e[0][m] = buf[t * 9 + m]; e[1][m] = buf[(t + 128) * 9 + m]; }
          dft8<-1>(e[0]);
          dft8<-1>(e[1]);
          named_bar(3, 128);
          if (it == 0) {
            constexpr float SC = 1.0f / (2048.0f * 512.0f);
#pragma unroll
            for (int i = 0; i < 16; i++)
              buf[128 * i + t] = cconj(cmul(e[i & 1][O8(i >> 1)], make_float2(bflo(wq[i]) * SC, bfhi(wq[i]) * SC)));
          } else {
            float2* col = g_spec + (size_t)(c0 + c) * S_ + t;
#pragma unroll
            for (int i = 0; i < 16; i++) col[128 * i] = cconj(e[i & 1][O8(i >> 1)]);
          }
        }
      }
    }
    named_bar(3, 128);
    if (t == 0) {
      TS(14);
      const unsigned target = grid_arrive(&g_bar[1]);
      if (!extra) {
        grid_wait(&g_bar[1], target);
        TS(15);
        fence_async();
        mbar_expect_tx(bar_tile, 32768);
        tma_load_2d(sb + SM_FFT, &maps.spec, s0, 0, bar_tile);
        mbar_wait(bar_g2, 0);
#pragma unroll 1
        for (int jq = 0; jq < NJOB; jq++) {
          unsigned* fl = &g_flag[(rt * NJOB + jq) * 8 + sp];
          int it = 0;
          while (ld_acquire(fl) < 8u) {
            if (++it > (1 << 22)) __trap();
          }
          *fl = 0u;
          fence_async();
          mbar_expect_tx(bar_g + 8 * jq, 32768);
          asm volatile("cp.async.bulk.shared::cluster.global.mbarrier::complete_tx::bytes [%0], [%1], %2, [%3];"
                       ::"r"(sb + jq * 32768), "l"(g_part + (((size_t)rt * NJOB + jq) * 8 + sp) * 8 * 256), "r"(32768), "r"(bar_g + 8 * jq) : "memory");
        }
      }
    }
  } else {
    if (blockIdx.x == 128) return;
    const int tid = threadIdx.x;
    const int r = tid & 15, q = tid >> 4;
    if (tid < 112) reinterpret_cast<uint32_t*>(smem + SM_B1)[tid] = __ldg(reinterpret_cast<const uint32_t*>(b1 + sp * FC) + tid);
#pragma unroll 1
    for (int ph = 0; ph < 2; ph++) {
      if (ph == 0) {
        uint32_t w[16];
        const uint32_t* xw = reinterpret_cast<const uint32_t*>(x + (size_t)(s0 + q) * D_);
#pragma unroll
        for (int n1 = 0; n1 < 16; n1++) w[n1] = __ldg(xw + 16 * n1 + r);
        float sum = 0.f;
#pragma unroll
        for (int n1 = 0; n1 < 16; n1++) sum += bflo(w[n1]) + bfhi(w[n1]);
#pragma unroll
        for (int o = 1; o < 16; o <<= 1) sum += __shfl_xor_sync(0xffffffffu, sum, o);
        const float mean = sum * (1.0f / D_);
        float sq = 0.f;
#pragma unroll
        for (int n1 = 0; n1 < 16; n1++) {
          float a = bflo(w[n1]) - mean, c = bfhi(w[n1]) - mean;
          sq += a * a + c * c;
        }
#pragma unroll
        for (int o = 1; o < 16; o <<= 1) sq += __shfl_xor_sync(0xffffffffu, sq, o);
        const uint32_t nm2 = pack_bf16(-mean, -mean);
        float sd, rs;
        asm("sqrt.approx.f32 %0, %1;" : "=f"(sd) : "f"(bf16r(bf16r(sq * (1.0f / D_)) + 1e-5f)));
        asm("rcp.approx.f32 %0, %1;" : "=f"(rs) : "f"(bf16r(sd)));
        if (r == 0) g_stats[s0 + q] = make_float2(-bflo(nm2), rs);
#pragma unroll
        for (int n1 = 0; n1 < 16; n1++) {
          const uint32_t d = hadd2_bf16(w[n1], nm2);
          const uint32_t xn = pack_bf16(bflo(d) * rs, bfhi(d) * rs);
          *tile_at(tile, 16 * n1 + r, q) = make_float2(bflo(xn), bfhi(xn));
        }
      } else {
        mbar_wait(bar_tile, 0);
        if (tid == 0) TS(17);
        const float y256 = __ldcg(&g_spec[(size_t)256 * S_ + s0 + r]).x;
#pragma unroll 2
        for (int i = 0; i < 8; i++) {
          const int j = q + 16 * i;
          float2* pa = tile_at(tile, j, r);
          float2* pb = tile_at(tile, j == 0 ? 128 : 256 - j, r);
          const float2 yk = *pa, ym = *pb;
          const float2 Sx = make_float2(yk.x + ym.x, yk.y - ym.y), Dx = make_float2(yk.x - ym.x, yk.y + ym.y);
          const float2 tw = twcs<512>(j);
          const float2 T = mulw<1>(Dx, tw.x, tw.y);
          *pa = j ? make_float2(Sx.x - T.y, -Sx.y - T.x) : make_float2(yk.x + y256, y256 - yk.x);
          *pb = j ? make_float2(Sx.x + T.y, Sx.y - T.x) : make_float2(2.f * ym.x, 2.f * ym.y);
        }
      }
      named_bar(1, 256);
      {
        uint8_t* pa = reinterpret_cast<uint8_t*>(tile_at(tile, q, r));
        const uint8_t* pb = tile + q * 2048 + (r & 1) * 8;
#pragma unroll 1
        for (int p = 0; p < 2; p++) {
          float2 v[16];
#pragma unroll
          for (int i = 0; i < 16; i++)
            v[i] = *reinterpret_cast<const float2*>(p ? pb + i * 128 + ((((r >> 1) ^ i) & 7) << 4) : pa + i * 2048);
          dft16<-1>(v);
          if (p == 0) twiddle16(v, 8 * q);
          named_bar(1, 256);
          if (p & ph) {
#pragma unroll
            for (int i = 0; i < 16; i++) reinterpret_cast<uint32_t*>(tile)[r * SPITCH + q + 16 * i] = pack_bf16(v[O16(i)].x, -v[O16(i)].y);
          } else {
#pragma unroll
            for (int i = 0; i < 16; i++) *reinterpret_cast<float2*>(pa + i * 2048) = v[O16(i)];
          }
          named_bar(1, 256);
        }
      }
      if (ph == 1) break;
      if (tid == 0) TS(10);
#pragma unroll 2
      for (int i = 0; i < 8; i++) {
        const int j = q + 16 * i;
        float2* pa = tile_at(tile, j, r);
        float2* pb = tile_at(tile, j == 0 ? 128 : 256 - j, r);
        const float2 A = *pa, Zb = *pb;
        const float2 E = make_float2(0.5f * (A.x + Zb.x), 0.5f * (A.y - Zb.y));
        const float2 O = make_float2(0.5f * (A.y + Zb.y), -0.5f * (A.x - Zb.x));
        const float2 tw = twcs<512>(j);
        const float2 T = mulw<-1>(O, tw.x, tw.y);
        if (j == 0) g_spec[(size_t)256 * S_ + s0 + r] = make_float2(A.x - A.y, 0.f);
        *pa = j ? make_float2(E.x + T.x, E.y + T.y) : make_float2(A.x + A.y, 0.f);
        *pb = j ? make_float2(E.x - T.x, T.y - E.y) : cconj(Zb);
      }
      fence_async();
      __threadfence();
      mbar_arrive(bar_p1);

      gemm_part(smem, maps, rt, sp);
    }
    if (tid == 0) TS(16);
    {
      const int g = lane >> 2;
      const uint32_t* stile = reinterpret_cast<const uint32_t*>(tile);
#pragma unroll 1
      for (int jq = 0; jq < NJOB; jq++) {
        const int cw = jq * 64 + 8 * warp + (lane & 3);
        uint32_t bw[2], xw[4];
#pragma unroll
        for (int c = 0; c < 4; c++) {
          if (!(c & 1)) bw[c >> 1] = __ldg(reinterpret_cast<const uint32_t*>(b2) + cw + 4 * (c >> 1));
          xw[c] = __ldg(reinterpret_cast<const uint32_t*>(x) + (size_t)(s0 + g + 8 * (c & 1)) * 256 + cw + 4 * (c >> 1));
        }
        mbar_wait(bar_g + 8 * jq, 0);
        const uint4* src = reinterpret_cast<const uint4*>(smem + jq * 32768) + tid;
        float o[8];
#pragma unroll
        for (int c = 0; c < 8; c++) o[c] = 0.f;
#pragma unroll
        for (int s = 0; s < 8; s++) {
          const uint4 v = src[s * 256];
          o[0] += bflo(v.x); o[1] += bfhi(v.x); o[2] += bflo(v.y); o[3] += bfhi(v.y);
          o[4] += bflo(v.z); o[5] += bfhi(v.z); o[6] += bflo(v.w); o[7] += bfhi(v.w);
        }
#pragma unroll
        for (int c = 0; c < 4; c++) {
          const int row = g + 8 * (c & 1), w = cw + 4 * (c >> 1);
          const uint32_t sw = stile[row * SPITCH + w];
          const uint32_t p = hadd2_bf16(pack_bf16(0.5f * o[2 * c], 0.5f * o[2 * c + 1]), bw[c >> 1]);
          const float oa = bflo(p), ob = bfhi(p);
          const uint32_t gg = pack_bf16(__fdividef(oa, 1.0f + __expf(-oa)), __fdividef(ob, 1.0f + __expf(-ob)));
          const uint32_t sg = pack_bf16(bflo(sw) * bflo(gg), bfhi(sw) * bfhi(gg));
          reinterpret_cast<uint32_t*>(out)[(size_t)(s0 + row) * 256 + w] = hadd2_bf16(xw[c], sg);
        }
        if (tid == 0) TS(20 + jq);
      }
    }
  }
}

typedef CUresult (*EncodeFn)(CUtensorMap*, CUtensorMapDataType, cuuint32_t, void*, const cuuint64_t*, const cuuint64_t*,
                             const cuuint32_t*, const cuuint32_t*, CUtensorMapInterleave, CUtensorMapSwizzle,
                             CUtensorMapL2promotion, CUtensorMapFloatOOBfill);

}

extern "C" void kernel_launch(void* const* d_in, const int* in_sizes, int n_in, void* d_out, int out_size) {
  const __nv_bfloat16* x = (const __nv_bfloat16*)d_in[0];
  const __nv_bfloat16* wr = (const __nv_bfloat16*)d_in[1];
  const __nv_bfloat16* wi = (const __nv_bfloat16*)d_in[2];
  const __nv_bfloat16* w1 = (const __nv_bfloat16*)d_in[4];
  const __nv_bfloat16* b1 = (const __nv_bfloat16*)d_in[5];
  const __nv_bfloat16* w2 = (const __nv_bfloat16*)d_in[6];
  const __nv_bfloat16* b2 = (const __nv_bfloat16*)d_in[7];
  __nv_bfloat16* out = (__nv_bfloat16*)d_out;

  static EncodeFn enc = nullptr;
  static void* p_spec = nullptr;
  static void* p_wt = nullptr;
  if (!enc) {
    void* fn = nullptr;
    cudaDriverEntryPointQueryResult qr;
    cudaGetDriverEntryPoint("cuTensorMapEncodeTiled", &fn, cudaEnableDefault, &qr);
    enc = (EncodeFn)fn;
    cudaFuncSetAttribute(k_mega, cudaFuncAttributeMaxDynamicSharedMemorySize, SM_TOTAL);
    cudaGetSymbolAddress(&p_spec, g_spec);
    cudaGetSymbolAddress(&p_wt, g_wt);
  }
  Maps m;
  const cuuint32_t es[3] = {1, 1, 1};
  {
    cuuint64_t dims[2] = {(cuuint64_t)D_, (cuuint64_t)S_};
    cuuint64_t strides[1] = {(cuuint64_t)D_ * 2};
    cuuint32_t box[2] = {64, 128};
    enc(&m.x, CU_TENSOR_MAP_DATA_TYPE_BFLOAT16, 2, (void*)x, dims, strides, box, es, CU_TENSOR_MAP_INTERLEAVE_NONE,
        CU_TENSOR_MAP_SWIZZLE_128B, CU_TENSOR_MAP_L2_PROMOTION_L2_128B, CU_TENSOR_MAP_FLOAT_OOB_FILL_NONE);
  }
  {
    cuuint64_t dims[3] = {32, 512, 56};
    cuuint64_t strides[2] = {(cuuint64_t)F_ * 2, 64};
    cuuint32_t box[3] = {32, 32, 7};
    enc(&m.w1, CU_TENSOR_MAP_DATA_TYPE_BFLOAT16, 3, (void*)w1, dims, strides, box, es, CU_TENSOR_MAP_INTERLEAVE_NONE,
        CU_TENSOR_MAP_SWIZZLE_64B, CU_TENSOR_MAP_L2_PROMOTION_L2_128B, CU_TENSOR_MAP_FLOAT_OOB_FILL_NONE);
  }
  {
    cuuint64_t dims[2] = {(cuuint64_t)D_, (cuuint64_t)F_};
    cuuint64_t strides[1] = {(cuuint64_t)D_ * 2};
    cuuint32_t box[2] = {64, 112};
    enc(&m.w2, CU_TENSOR_MAP_DATA_TYPE_BFLOAT16, 2, (void*)w2, dims, strides, box, es, CU_TENSOR_MAP_INTERLEAVE_NONE,
        CU_TENSOR_MAP_SWIZZLE_128B, CU_TENSOR_MAP_L2_PROMOTION_L2_128B, CU_TENSOR_MAP_FLOAT_OOB_FILL_NONE);
  }
  {
    cuuint64_t dims[2] = {(cuuint64_t)S_, 256};
    cuuint64_t strides[1] = {(cuuint64_t)S_ * 8};
    cuuint32_t box[2] = {16, 256};
    enc(&m.spec, CU_TENSOR_MAP_DATA_TYPE_FLOAT64, 2, p_spec, dims, strides, box, es, CU_TENSOR_MAP_INTERLEAVE_NONE,
        CU_TENSOR_MAP_SWIZZLE_128B, CU_TENSOR_MAP_L2_PROMOTION_NONE, CU_TENSOR_MAP_FLOAT_OOB_FILL_NONE);
  }
  {
    cuuint64_t dims[2] = {(cuuint64_t)S_, 257};
    cuuint64_t strides[1] = {(cuuint64_t)S_ * 4};
    cuuint32_t box[2] = {16, 32};
    enc(&m.wt, CU_TENSOR_MAP_DATA_TYPE_UINT32, 2, p_wt, dims, strides, box, es, CU_TENSOR_MAP_INTERLEAVE_NONE,
        CU_TENSOR_MAP_SWIZZLE_64B, CU_TENSOR_MAP_L2_PROMOTION_NONE, CU_TENSOR_MAP_FLOAT_OOB_FILL_NONE);
  }
  k_mega<<<129, NTHREADS, SM_TOTAL>>>(x, wr, wi, b1, b2, out, m);
}
```

```cpp
#include <cuda_runtime.h>
#include <cuda_bf16.h>
#include <cuda.h>
#include <stdint.h>

namespace {

constexpr int S_ = 2048, D_ = 512, F_ = 1792, DF_ = 257;
constexpr int FC = 224;
constexpr int NJOB = 4;

__device__ __align__(1024) float2 g_spec[257 * 2048];
__device__ __align__(1024) uint32_t g_wt[257 * 2048];
__device__ uint4 g_part[16 * NJOB * 8 * 8 * 256];
__device__ float2 g_cs[8 * 32 * 112];
__device__ float2 g_stats[2048];
__device__ unsigned g_bar[2];
__device__ unsigned g_flag[16 * NJOB * 8];
#define TS(i)

__device__ __forceinline__ uint32_t smem_u32(const void* p) { return (uint32_t)__cvta_generic_to_shared(p); }
__device__ __forceinline__ float bf16r(float x) { return __bfloat162float(__float2bfloat16_rn(x)); }
__device__ __forceinline__ float bflo(uint32_t w) { return __uint_as_float(w << 16); }
__device__ __forceinline__ float bfhi(uint32_t w) { return __uint_as_float(w & 0xffff0000u); }
__device__ __forceinline__ uint32_t pack_bf16(float lo, float hi) {
  uint32_t r;
  asm("cvt.rn.bf16x2.f32 %0, %1, %2;" : "=r"(r) : "f"(hi), "f"(lo));
  return r;
}
__device__ __forceinline__ uint32_t hadd2_bf16(uint32_t a, uint32_t b) {
  uint32_t r;
  asm("add.rn.bf16x2 %0, %1, %2;" : "=r"(r) : "r"(a), "r"(b));
  return r;
}
__device__ __forceinline__ void named_bar(int id, int n) { asm volatile("bar.sync %0, %1;" ::"r"(id), "r"(n) : "memory"); }
__device__ __forceinline__ void fence_async() { asm volatile("fence.proxy.async;" ::: "memory"); }

__device__ __forceinline__ void mbar_init(uint32_t bar, int cnt) { asm volatile("mbarrier.init.shared::cta.b64 [%0], %1;" ::"r"(bar), "r"(cnt) : "memory"); }
__device__ __forceinline__ void mbar_expect_tx(uint32_t bar, uint32_t bytes) { asm volatile("mbarrier.arrive.expect_tx.shared::cta.b64 _, [%0], %1;" ::"r"(bar), "r"(bytes) : "memory"); }
__device__ __forceinline__ void mbar_arrive(uint32_t bar) { asm volatile("mbarrier.arrive.shared::cta.b64 _, [%0];" ::"r"(bar) : "memory"); }
__device__ __forceinline__ bool mbar_try(uint32_t bar, uint32_t parity) {
  uint32_t ok;
  asm volatile("{\n.reg .pred p;\nmbarrier.try_wait.parity.shared::cta.b64 p, [%1], %2, %3;\nselp.u32 %0, 1, 0, p;\n}\n" : "=r"(ok) : "r"(bar), "r"(parity), "r"(20000u) : "memory");
  return ok != 0;
}
__device__ __forceinline__ void mbar_wait(uint32_t bar, uint32_t parity) {
  int it = 0;
  while (!mbar_try(bar, parity)) {
    if (++it > (1 << 22)) __trap();
  }
}
__device__ __forceinline__ void tma_load_3d(uint32_t dst, const CUtensorMap* map, int c0, int c1, int c2, uint32_t bar) {
  asm volatile("cp.async.bulk.tensor.3d.shared::cluster.global.mbarrier::complete_tx::bytes [%0], [%1, {%3, %4, %5}], [%2];"
               ::"r"(dst), "l"((uint64_t)map), "r"(bar), "r"(c0), "r"(c1), "r"(c2) : "memory");
}
__device__ __forceinline__ void tma_load_2d(uint32_t dst, const CUtensorMap* map, int c0, int c1, uint32_t bar) {
  asm volatile("cp.async.bulk.tensor.2d.shared::cluster.global.mbarrier::complete_tx::bytes [%0], [%1, {%3, %4}], [%2];"
               ::"r"(dst), "l"((uint64_t)map), "r"(bar), "r"(c0), "r"(c1) : "memory");
}
__device__ __forceinline__ void tma_store_2d(const CUtensorMap* map, int c0, int c1, uint32_t src) {
  asm volatile("cp.async.bulk.tensor.2d.global.shared::cta.bulk_group [%0, {%2, %3}], [%1];"
               ::"l"((uint64_t)map), "r"(src), "r"(c0), "r"(c1) : "memory");
}
__device__ __forceinline__ void tma_store_commit_wait() {
  asm volatile("cp.async.bulk.commit_group;" ::: "memory");
  asm volatile("cp.async.bulk.wait_group 0;" ::: "memory");
}
__device__ __forceinline__ void wgmma_fence() { asm volatile("wgmma.fence.sync.aligned;" ::: "memory"); }
__device__ __forceinline__ void wgmma_commit() { asm volatile("wgmma.commit_group.sync.aligned;" ::: "memory"); }
template <int N> __device__ __forceinline__ void wgmma_wait() { asm volatile("wgmma.wait_group.sync.aligned %0;" ::"n"(N) : "memory"); }
__device__ __forceinline__ uint64_t make_desc(uint32_t addr, uint32_t lbo_bytes, uint32_t sbo_bytes, uint32_t swz) {
  uint64_t d = 0;
  d |= (uint64_t)((addr & 0x3FFFF) >> 4);
  d |= (uint64_t)((lbo_bytes & 0x3FFFF) >> 4) << 16;
  d |= (uint64_t)((sbo_bytes & 0x3FFFF) >> 4) << 32;
  d |= (uint64_t)swz << 62;
  return d;
}
__device__ __forceinline__ unsigned ld_acquire(const unsigned* p) {
  unsigned v;
  asm volatile("ld.acquire.gpu.global.u32 %0, [%1];" : "=r"(v) : "l"(p) : "memory");
  return v;
}

__device__ __forceinline__ void wgmma_n224_ss(float (&d)[112], uint64_t da, uint64_t db, int scale_d) {
  asm volatile("{\n.reg .pred p;\nsetp.ne.b32 p, %114, 0;\n"
    "wgmma.mma_async.sync.aligned.m64n224k16.f32.bf16.bf16 {%0, %1, %2, %3, %4, %5, %6, %7, %8, %9, %10, %11, %12, %13, %14, %15, %16, %17, %18, %19, %20, %21, %22, %23, %24, %25, %26, %27, %28, %29, %30, %31, %32, %33, %34, %35, %36, %37, %38, %39, %40, %41, %42, %43, %44, %45, %46, %47, %48, %49, %50, %51, %52, %53, %54, %55, %56, %57, %58, %59, %60, %61, %62, %63, %64, %65, %66, %67, %68, %69, %70, %71, %72, %73, %74, %75, %76, %77, %78, %79, %80, %81, %82, %83, %84, %85, %86, %87, %88, %89, %90, %91, %92, %93, %94, %95, %96, %97, %98, %99, %100, %101, %102, %103, %104, %105, %106, %107, %108, %109, %110, %111}, %112, %113, p, 1, 1, 0, 1;\n}\n"
    : "+f"(d[0]), "+f"(d[1]), "+f"(d[2]), "+f"(d[3]), "+f"(d[4]), "+f"(d[5]), "+f"(d[6]), "+f"(d[7]), "+f"(d[8]), "+f"(d[9]), "+f"(d[10]), "+f"(d[11]), "+f"(d[12]), "+f"(d[13]), "+f"(d[14]), "+f"(d[15]), "+f"(d[16]), "+f"(d[17]), "+f"(d[18]), "+f"(d[19]), "+f"(d[20]), "+f"(d[21]), "+f"(d[22]), "+f"(d[23]), "+f"(d[24]), "+f"(d[25]), "+f"(d[26]), "+f"(d[27]), "+f"(d[28]), "+f"(d[29]), "+f"(d[30]), "+f"(d[31]), "+f"(d[32]), "+f"(d[33]), "+f"(d[34]), "+f"(d[35]), "+f"(d[36]), "+f"(d[37]), "+f"(d[38]), "+f"(d[39]), "+f"(d[40]), "+f"(d[41]), "+f"(d[42]), "+f"(d[43]), "+f"(d[44]), "+f"(d[45]), "+f"(d[46]), "+f"(d[47]), "+f"(d[48]), "+f"(d[49]), "+f"(d[50]), "+f"(d[51]), "+f"(d[52]), "+f"(d[53]), "+f"(d[54]), "+f"(d[55]), "+f"(d[56]), "+f"(d[57]), "+f"(d[58]), "+f"(d[59]), "+f"(d[60]), "+f"(d[61]), "+f"(d[62]), "+f"(d[63]), "+f"(d[64]), "+f"(d[65]), "+f"(d[66]), "+f"(d[67]), "+f"(d[68]), "+f"(d[69]), "+f"(d[70]), "+f"(d[71]), "+f"(d[72]), "+f"(d[73]), "+f"(d[74]), "+f"(d[75]), "+f"(d[76]), "+f"(d[77]), "+f"(d[78]), "+f"(d[79]), "+f"(d[80]), "+f"(d[81]), "+f"(d[82]), "+f"(d[83]), "+f"(d[84]), "+f"(d[85]), "+f"(d[86]), "+f"(d[87]), "+f"(d[88]), "+f"(d[89]), "+f"(d[90]), "+f"(d[91]), "+f"(d[92]), "+f"(d[93]), "+f"(d[94]), "+f"(d[95]), "+f"(d[96]), "+f"(d[97]), "+f"(d[98]), "+f"(d[99]), "+f"(d[100]), "+f"(d[101]), "+f"(d[102]), "+f"(d[103]), "+f"(d[104]), "+f"(d[105]), "+f"(d[106]), "+f"(d[107]), "+f"(d[108]), "+f"(d[109]), "+f"(d[110]), "+f"(d[111])
    : "l"(da), "l"(db), "r"(scale_d));
}
__device__ __forceinline__ void wgmma_n128_rs(float (&d)[64], uint32_t a0, uint32_t a1, uint32_t a2, uint32_t a3, uint64_t db, int scale_d) {
  asm volatile("{\n.reg .pred p;\nsetp.ne.b32 p, %69, 0;\n"
    "wgmma.mma_async.sync.aligned.m64n128k16.f32.bf16.bf16 {%0, %1, %2, %3, %4, %5, %6, %7, %8, %9, %10, %11, %12, %13, %14, %15, %16, %17, %18, %19, %20, %21, %22, %23, %24, %25, %26, %27, %28, %29, %30, %31, %32, %33, %34, %35, %36, %37, %38, %39, %40, %41, %42, %43, %44, %45, %46, %47, %48, %49, %50, %51, %52, %53, %54, %55, %56, %57, %58, %59, %60, %61, %62, %63}, {%64, %65, %66, %67}, %68, p, 1, 1, 1;\n}\n"
    : "+f"(d[0]), "+f"(d[1]), "+f"(d[2]), "+f"(d[3]), "+f"(d[4]), "+f"(d[5]), "+f"(d[6]), "+f"(d[7]), "+f"(d[8]), "+f"(d[9]), "+f"(d[10]), "+f"(d[11]), "+f"(d[12]), "+f"(d[13]), "+f"(d[14]), "+f"(d[15]), "+f"(d[16]), "+f"(d[17]), "+f"(d[18]), "+f"(d[19]), "+f"(d[20]), "+f"(d[21]), "+f"(d[22]), "+f"(d[23]), "+f"(d[24]), "+f"(d[25]), "+f"(d[26]), "+f"(d[27]), "+f"(d[28]), "+f"(d[29]), "+f"(d[30]), "+f"(d[31]), "+f"(d[32]), "+f"(d[33]), "+f"(d[34]), "+f"(d[35]), "+f"(d[36]), "+f"(d[37]), "+f"(d[38]), "+f"(d[39]), "+f"(d[40]), "+f"(d[41]), "+f"(d[42]), "+f"(d[43]), "+f"(d[44]), "+f"(d[45]), "+f"(d[46]), "+f"(d[47]), "+f"(d[48]), "+f"(d[49]), "+f"(d[50]), "+f"(d[51]), "+f"(d[52]), "+f"(d[53]), "+f"(d[54]), "+f"(d[55]), "+f"(d[56]), "+f"(d[57]), "+f"(d[58]), "+f"(d[59]), "+f"(d[60]), "+f"(d[61]), "+f"(d[62]), "+f"(d[63])
    : "r"(a0), "r"(a1), "r"(a2), "r"(a3), "l"(db), "r"(scale_d));
}

__device__ __forceinline__ float2 cadd(float2 a, float2 b) { return make_float2(a.x + b.x, a.y + b.y); }
__device__ __forceinline__ float2 csub(float2 a, float2 b) { return make_float2(a.x - b.x, a.y - b.y); }
__device__ __forceinline__ float2 cmul(float2 a, float2 b) { return make_float2(a.x * b.x - a.y * b.y, a.x * b.y + a.y * b.x); }
__device__ __forceinline__ float2 cconj(float2 a) { return make_float2(a.x, -a.y); }

template <int DIR> __device__ __forceinline__ void dft4(float2& a0, float2& a1, float2& a2, float2& a3) {
  float2 t0 = cadd(a0, a2), t1 = csub(a0, a2), t2 = cadd(a1, a3), t3 = csub(a1, a3);
  float2 t3r = DIR < 0 ? make_float2(t3.y, -t3.x) : make_float2(-t3.y, t3.x);
  a0 = cadd(t0, t2); a2 = csub(t0, t2); a1 = cadd(t1, t3r); a3 = csub(t1, t3r);
}
template <int DIR> __device__ __forceinline__ float2 mulw(float2 v, float c, float s) {
  return DIR < 0 ? make_float2(v.x * c + v.y * s, v.y * c - v.x * s) : make_float2(v.x * c - v.y * s, v.y * c + v.x * s);
}
template <int DIR> __device__ __forceinline__ float2 muli(float2 v) {
  return DIR < 0 ? make_float2(v.y, -v.x) : make_float2(-v.y, v.x);
}
#define O16(k) (4 * ((k) & 3) + ((k) >> 2))
#define O8(k) (2 * ((k) & 3) + ((k) >> 2))
template <int DIR> __device__ __forceinline__ void dft16(float2 (&v)[16]) {
  constexpr float C1 = 0.92387953251128674f, S1 = 0.38268343236508977f, R = 0.70710678118654752f;
#pragma unroll
  for (int n2 = 0; n2 < 4; n2++) dft4<DIR>(v[n2], v[4 + n2], v[8 + n2], v[12 + n2]);
  v[5] = mulw<DIR>(v[5], C1, S1);
  v[6] = mulw<DIR>(v[6], R, R);
  v[7] = mulw<DIR>(v[7], S1, C1);
  v[9] = mulw<DIR>(v[9], R, R);
  v[10] = muli<DIR>(v[10]);
  v[11] = mulw<DIR>(v[11], -R, R);
  v[13] = mulw<DIR>(v[13], S1, C1);
  v[14] = mulw<DIR>(v[14], -R, R);
  v[15] = mulw<DIR>(v[15], -C1, -S1);
#pragma unroll
  for (int k1 = 0; k1 < 4; k1++) dft4<DIR>(v[4 * k1], v[4 * k1 + 1], v[4 * k1 + 2], v[4 * k1 + 3]);
}
template <int DIR> __device__ __forceinline__ void dft8(float2 (&v)[8]) {
  constexpr float R = 0.70710678118654752f;
  dft4<DIR>(v[0], v[2], v[4], v[6]);
  dft4<DIR>(v[1], v[3], v[5], v[7]);
  v[3] = mulw<DIR>(v[3], R, R);
  v[5] = muli<DIR>(v[5]);
  v[7] = mulw<DIR>(v[7], -R, R);
#pragma unroll
  for (int k1 = 0; k1 < 4; k1++) {
    float2 a = v[2 * k1], b = v[2 * k1 + 1];
    v[2 * k1] = cadd(a, b); v[2 * k1 + 1] = csub(a, b);
  }
}
template <int N> __device__ __forceinline__ float2 twcs(int m) {
  m &= (N - 1);
  if (m >= N / 2) m -= N;
  float s, c;
  __sincosf((float)m * (6.283185307179586f / N), &s, &c);
  return make_float2(c, s);
}

__device__ __forceinline__ void twiddle16(float2 (&v)[16], int m) {
  const float2 w1 = twcs<2048>(m);
  float2 w = w1;
#pragma unroll
  for (int k = 1; k < 16; k++) {
    v[O16(k)] = mulw<-1>(v[O16(k)], w.x, w.y);
    if (k < 15) w = cmul(w, w1);
  }
}
__device__ __forceinline__ float2* tile_at(uint8_t* tile, int k, int r) {
  return reinterpret_cast<float2*>(tile + k * 128 + ((((r >> 1) ^ k) & 7) << 4) + (r & 1) * 8);
}
constexpr int SPITCH = 260;

constexpr int STEP = 45056;
constexpr int W1_STAGE = 14336;
constexpr int SM_FFT = 184 * 1024;
constexpr int SM_WT = SM_FFT + 32768;
constexpr int SM_BAR = SM_WT + 8192;
constexpr int SM_TOTAL = SM_BAR + 256;
constexpr int NTHREADS = 384;

__device__ __forceinline__ float gelu2(float x) {
  float u = x * (0.7978845608028654f + 0.035677408136300125f * x * x);
  float th;
  asm("tanh.approx.f32 %0, %1;" : "=f"(th) : "f"(u));
  return fmaf(x, th, x);
}
__device__ __forceinline__ unsigned grid_arrive(unsigned* cnt) {
  __threadfence();
  unsigned old = atomicAdd(cnt, 1u);
  return (old / 129u + 1u) * 129u;
}
__device__ __forceinline__ void grid_wait(const unsigned* cnt, unsigned target) {
  int it = 0;
  while ((int)(ld_acquire(cnt) - target) < 0) {
    if (++it > (1 << 22)) __trap();
  }
}
__device__ __forceinline__ uint32_t piece_off(int p) {
  if (p >= 12) p -= 12;
  const int s = (p * 11) >> 5;
  return (uint32_t)(s * STEP + (p - 3 * s) * W1_STAGE);
}

struct Maps { CUtensorMap x, w1, w2, spec, wt; };

__device__ __forceinline__ void load_step(uint32_t sb, const Maps& maps, int rt, int sp, int j) {
  const uint32_t dst = sb + (j & 3) * STEP, bar = sb + SM_BAR + 8 * (j & 3);
  mbar_expect_tx(bar, STEP);
  tma_load_2d(dst, &maps.x, j * 64, rt * 128, bar);
  tma_load_3d(dst + 16384, &maps.w1, 0, j * 64, sp * 7, bar);
  tma_load_3d(dst + 16384 + W1_STAGE, &maps.w1, 0, j * 64 + 32, sp * 7, bar);
}
__device__ __forceinline__ void load_piece(uint32_t sb, const Maps& maps, int sp, int p) {
  const uint32_t bar = sb + SM_BAR + 64 + 8 * (p >> 1);
  mbar_expect_tx(bar, W1_STAGE);
  tma_load_2d(sb + piece_off(p), &maps.w2, (p >> 2) * 128 + (p & 1) * 64, sp * FC + ((p >> 1) & 1) * 112, bar);
}

__device__ __forceinline__ void gemm_part(uint8_t* smem, const Maps& maps, const __nv_bfloat16* __restrict__ b1, int rt, int sp) {
  const uint32_t sb = smem_u32(smem);
  const int tid = threadIdx.x, warp = tid >> 5, lane = tid & 31, wg = warp >> 2;
  const uint32_t bar_full1 = sb + SM_BAR, bar_full2 = sb + SM_BAR + 64;
  unsigned* relcnt = reinterpret_cast<unsigned*>(smem + SM_BAR + 128);
  const uint32_t bar_stats = sb + SM_BAR + 160, bar_st = sb + SM_BAR + 224;
  uint32_t ha[56];
      auto release = [&](int j) {
        __syncwarp();
        if (lane == 0) {
          __threadfence_block();
          if ((atomicAdd(&relcnt[j & 3], 1u) & 7u) == 7u) {
            __threadfence_block();
            if (j < 4) load_step(sb, maps, rt, sp, j + 4);
            else {
#pragma unroll 1
              for (int p = 3 * (j - 4); p < 3 * (j - 4) + 3; p++) load_piece(sb, maps, sp, p);
            }
          }
        }
      };
      {
        float acc[112];
#pragma unroll
        for (int i = 0; i < 112; i++) acc[i] = 0.f;
#pragma unroll 1
        for (int j = 0; j < 8; j++) {
          const uint32_t base = (j & 3) * STEP;
          mbar_wait(bar_full1 + 8 * (j & 3), j >> 2);
          if (tid == 0) TS(24 + j);
          wgmma_fence();
#pragma unroll
          for (int kk = 0; kk < 4; kk++)
            wgmma_n224_ss(acc, make_desc(sb + base + wg * 8192 + kk * 32, 16, 1024, 1),
                          make_desc(sb + base + 16384 + (kk >> 1) * W1_STAGE + (kk & 1) * 1024, 2048, 512, 2), 1);
          wgmma_commit();
          if (j > 0) {
            wgmma_wait<1>();
            release(j - 1);
          }
        }
        wgmma_wait<0>();
        if (tid == 0) TS(2);
        mbar_wait(bar_stats, 0);
        if (tid < 224) {
          float c0 = 0.f, c1 = 0.f;
#pragma unroll
          for (int i = 0; i < 16; i++) { const float2 c = __ldcg(&g_cs[(sp * 32 + (tid & 1) * 16 + i) * 112 + (tid >> 1)]); c0 += c.x; c1 += c.y; }
          c0 += __shfl_xor_sync(0xffffffffu, c0, 1); c1 += __shfl_xor_sync(0xffffffffu, c1, 1);
          const uint32_t bw = __ldg(reinterpret_cast<const uint32_t*>(b1 + sp * FC) + (tid >> 1));
          reinterpret_cast<float4*>(smem + SM_WT)[tid >> 1] = make_float4(c0, c1, bflo(bw), bfhi(bw));
        }
        const int row = rt * 128 + warp * 16 + (lane >> 2);
        const float2 st0 = __ldcg(&g_stats[row]), st1 = __ldcg(&g_stats[row + 8]);
        named_bar(1, 256);
        if (tid == 0) {
#pragma unroll 1
          for (int p = 9; p < 12; p++) load_piece(sb, maps, sp, p);
        }
        if (tid == 0) TS(3);
        const float4* csb = reinterpret_cast<const float4*>(smem + SM_WT) + (lane & 3);
#pragma unroll
        for (int j = 0; j < 28; j++) {
          const float4 c = csb[j * 4];
          ha[2 * j] = pack_bf16(gelu2(fmaf(fmaf(-st0.x, c.x, acc[4 * j]), st0.y, c.z)), gelu2(fmaf(fmaf(-st0.x, c.y, acc[4 * j + 1]), st0.y, c.w)));
          ha[2 * j + 1] = pack_bf16(gelu2(fmaf(fmaf(-st1.x, c.x, acc[4 * j + 2]), st1.y, c.z)), gelu2(fmaf(fmaf(-st1.x, c.y, acc[4 * j + 3]), st1.y, c.w)));
        }
      }
      if (tid == 0) TS(4);
      if (wg == 1) named_bar(2, 256);
#pragma unroll 1
      for (int jq = 0; jq < NJOB; jq++) {
        float acc[64];
#pragma unroll
        for (int h = 0; h < 2; h++) {
          const uint32_t o0 = piece_off(4 * jq + 2 * h), o1 = piece_off(4 * jq + 2 * h + 1);
          mbar_wait(bar_full2 + 8 * (2 * jq + h), 0);
          wgmma_fence();
#pragma unroll
          for (int kk = 0; kk < 7; kk++) {
            const int kb = h * 7 + kk;
            wgmma_n128_rs(acc, ha[4 * kb], ha[4 * kb + 1], ha[4 * kb + 2], ha[4 * kb + 3],
                          make_desc(sb + o0 + kk * 2048, o1 - o0, 1024, 1), kb > 0);
          }
          wgmma_commit();
        }
        if (jq == 0 && wg == 0) asm volatile("bar.arrive 2, 256;" ::: "memory");
        wgmma_wait<0>();
        if (jq == 0 && lane == 0) {
          __threadfence_block();
          if (atomicAdd(&relcnt[4], 1u) == 7u) {
            __threadfence_block();
#pragma unroll 1
            for (int p = 12; p < 16; p++) load_piece(sb, maps, sp, p);
          }
        }
        uint4* dstp = g_part + ((((size_t)rt * NJOB + jq) * 8 + warp) * 8 + sp) * 256 + lane;
#pragma unroll
        for (int i = 0; i < 8; i++)
          dstp[i * 32] = make_uint4(pack_bf16(acc[8 * i], acc[8 * i + 1]), pack_bf16(acc[8 * i + 2], acc[8 * i + 3]),
                                    pack_bf16(acc[8 * i + 4], acc[8 * i + 5]), pack_bf16(acc[8 * i + 6], acc[8 * i + 7]));
        __syncwarp();
        if (lane == 0) mbar_arrive(bar_st + 8 * jq);
        if (tid == 0) TS(5 + jq);
      }
}

__global__ void __launch_bounds__(NTHREADS, 1)
k_mega(const __nv_bfloat16* __restrict__ x, const __nv_bfloat16* __restrict__ wr, const __nv_bfloat16* __restrict__ wi,
       const __nv_bfloat16* __restrict__ w1, const __nv_bfloat16* __restrict__ b1, const __nv_bfloat16* __restrict__ b2, __nv_bfloat16* __restrict__ out,
       const __grid_constant__ Maps maps) {
  extern __shared__ __align__(1024) uint8_t smem[];
  const uint32_t sb = smem_u32(smem);
  const int rt = blockIdx.x >> 3, sp = blockIdx.x & 7;
  const int warp = threadIdx.x >> 5, lane = threadIdx.x & 31;
  const int s0 = blockIdx.x * 16;
  if (threadIdx.x == 0) TS(0);
  const uint32_t bar_full1 = sb + SM_BAR;
  const uint32_t bar_full2 = sb + SM_BAR + 64;
  unsigned* relcnt = reinterpret_cast<unsigned*>(smem + SM_BAR + 128);
  const uint32_t bar_stats = sb + SM_BAR + 160;
  const uint32_t bar_p1 = sb + SM_BAR + 168;
  const uint32_t bar_tile = sb + SM_BAR + 176;
  const uint32_t bar_st = sb + SM_BAR + 224;
  const uint32_t bar_g = sb + SM_BAR + 192;
  uint8_t* tile = smem + SM_FFT;

  if (threadIdx.x == 0) {
    for (int i = 0; i < 4; i++) mbar_init(bar_full1 + 8 * i, 1);
    for (int i = 0; i < 8; i++) mbar_init(bar_full2 + 8 * i, 2);
    mbar_init(bar_stats, 1); mbar_init(bar_p1, 256); mbar_init(bar_tile, 1);
    for (int i = 0; i < 4; i++) { mbar_init(bar_g + 8 * i, 1); mbar_init(bar_st + 8 * i, 8); }
    for (int i = 0; i < 5; i++) relcnt[i] = 0;
    asm volatile("fence.mbarrier_init.release.cluster;" ::: "memory");
    if (blockIdx.x < 128) {
#pragma unroll 1
      for (int j = 0; j < 4; j++) load_step(sb, maps, rt, sp, j);
    }
  }
  __syncthreads();

  if (warp >= 8) {
    const int t = threadIdx.x & 127;
    const bool extra = blockIdx.x == 128;
    if (!extra) {
      const uint32_t stg = (uint32_t)(SM_WT + (warp - 8) * 2048);
      if (t < 16) {
        const size_t o = (size_t)(s0 + t) * DF_ + 256;
        g_wt[(size_t)256 * S_ + s0 + t] = (uint32_t)__ldg(reinterpret_cast<const unsigned short*>(wr) + o) |
                                          ((uint32_t)__ldg(reinterpret_cast<const unsigned short*>(wi) + o) << 16);
      }
      uint32_t wv[2][16];
      {
        const unsigned short* pr = reinterpret_cast<const unsigned short*>(wr) + (size_t)s0 * DF_ + t;
        const unsigned short* pi = reinterpret_cast<const unsigned short*>(wi) + (size_t)s0 * DF_ + t;
#pragma unroll
        for (int u = 0; u < 32; u++)
          wv[u >> 4][u & 15] = (uint32_t)__ldg(pr + (u & 15) * DF_ + (u >> 4) * 128) | ((uint32_t)__ldg(pi + (u & 15) * DF_ + (u >> 4) * 128) << 16);
      }
#pragma unroll
      for (int rd = 0; rd < 2; rd++) {
        if (rd && lane == 0) asm volatile("cp.async.bulk.wait_group.read 0;" ::: "memory");
        __syncwarp();
#pragma unroll
        for (int c = 0; c < 4; c++)
          *reinterpret_cast<uint4*>(smem + stg + lane * 64 + ((c ^ ((lane >> 1) & 3)) << 4)) =
              make_uint4(wv[rd][4 * c], wv[rd][4 * c + 1], wv[rd][4 * c + 2], wv[rd][4 * c + 3]);
        fence_async();
        __syncwarp();
        if (lane == 0) {
          tma_store_2d(&maps.wt, s0, rd * 128 + (warp - 8) * 32, sb + stg);
          asm volatile("cp.async.bulk.commit_group;" ::: "memory");
        }
      }
      if (lane == 0) { asm volatile("cp.async.bulk.wait_group 0;" ::: "memory"); __threadfence(); }
    }
    named_bar(3, 128);
    if (t == 0) {
      TS(11);
      if (!extra) {
        mbar_wait(bar_p1, 0);
        tma_store_2d(&maps.spec, s0, 0, sb + SM_FFT);
        tma_store_commit_wait();
      }
      TS(12);
      const unsigned target = grid_arrive(&g_bar[0]);
      grid_wait(&g_bar[0], target);
      mbar_arrive(bar_stats);
    }
    named_bar(3, 128);
    if (t == 0) TS(13);
    {
      float2* buf = reinterpret_cast<float2*>(tile);
      const int k1 = t >> 3, m2 = t & 7;
      const int c0 = extra ? 256 : blockIdx.x * 2, nc = extra ? 1 : 2;
      float2 vn[16];
      uint32_t wn[16];
#pragma unroll 1
      for (int c = -1; c < nc; c++) {
        uint32_t wq[16];
        if (c >= 0) {
#pragma unroll
          for (int i = 0; i < 16; i++) { buf[128 * i + t] = vn[i]; wq[i] = wn[i]; }
        }
        if (c + 1 < nc) {
#pragma unroll
          for (int i = 0; i < 16; i++) {
            vn[i] = __ldcg(g_spec + (size_t)(c0 + c + 1) * S_ + 128 * i + t);
            wn[i] = __ldcg(g_wt + (size_t)(c0 + c + 1) * S_ + 128 * i + t);
          }
        }
        if (c < 0) continue;
#pragma unroll 1
        for (int it = 0; it < 2; it++) {
#pragma unroll 1
          for (int p = 0; p < 2; p++) {
            const float2* in = buf + (p ? k1 * 136 + m2 : t);
            const int is = p ? 8 : 128;
            float2 v[16];
#pragma unroll
            for (int i = 0; i < 16; i++) v[i] = in[i * is];
            dft16<-1>(v);
            twiddle16(v, p ? 16 * m2 : t);
            named_bar(3, 128);
            float2* o = buf + (p ? k1 * 9 + m2 : t);
            const int os = p ? 144 : 136;
#pragma unroll
            for (int kk = 0; kk < 16; kk++) o[kk * os] = v[O16(kk)];
            named_bar(3, 128);
          }
          float2 e[2][8];
#pragma unroll
          for (int m = 0; m < 8; m++) { e[0][m] = buf[t * 9 + m]; e[1][m] = buf[(t + 128) * 9 + m]; }
          dft8<-1>(e[0]);
          dft8<-1>(e[1]);
          named_bar(3, 128);
          if (it == 0) {
            constexpr float SC = 1.0f / (2048.0f * 512.0f);
#pragma unroll
            for (int i = 0; i < 16; i++)
              buf[128 * i + t] = cconj(cmul(e[i & 1][O8(i >> 1)], make_float2(bflo(wq[i]) * SC, bfhi(wq[i]) * SC)));
          } else {
            float2* col = g_spec + (size_t)(c0 + c) * S_ + t;
#pragma unroll
            for (int i = 0; i < 16; i++) col[128 * i] = cconj(e[i & 1][O8(i >> 1)]);
          }
        }
      }
    }
    named_bar(3, 128);
    if (warp == 9 && lane < 8 && !extra) {
#pragma unroll 1
      for (int jq = 0; jq < NJOB; jq++) {
        mbar_wait(bar_st + 8 * jq, 0);
        __threadfence();
        atomicAdd(&g_flag[(rt * NJOB + jq) * 8 + lane], 1u);
      }
    }
    if (t == 64 && !extra) {
        mbar_wait(bar_st + 24, 0);
#pragma unroll 1
        for (int jq = 0; jq < NJOB; jq++) {
          unsigned* fl = &g_flag[(rt * NJOB + jq) * 8 + sp];
          int it = 0;
          while (ld_acquire(fl) < 8u) {
            if (++it > (1 << 22)) __trap();
          }
          *fl = 0u;
          fence_async();
          mbar_expect_tx(bar_g + 8 * jq, jq ? 32768 : 32768 + 17 * 1024);
          if (jq == 0) {
#pragma unroll 1
            for (int i = 0; i < 17; i++)
              asm volatile("cp.async.bulk.shared::cluster.global.mbarrier::complete_tx::bytes [%0], [%1], %2, [%3];"
                           ::"r"(sb + 131072 + i * SPITCH * 4), "l"(i < 16 ? x + (size_t)(s0 + i) * D_ : b2), "r"(1024), "r"(bar_g) : "memory");
          }
          asm volatile("cp.async.bulk.shared::cluster.global.mbarrier::complete_tx::bytes [%0], [%1], %2, [%3];"
                       ::"r"(sb + jq * 32768), "l"(g_part + (((size_t)rt * NJOB + jq) * 8 + sp) * 8 * 256), "r"(32768), "r"(bar_g + 8 * jq) : "memory");
        }
    }
    if (t == 0) {
      TS(14);
      const unsigned target = grid_arrive(&g_bar[1]);
      if (!extra) {
        grid_wait(&g_bar[1], target);
        TS(15);
        fence_async();
        mbar_expect_tx(bar_tile, 32768);
        tma_load_2d(sb + SM_FFT, &maps.spec, s0, 0, bar_tile);
      }
    }
  } else {
    if (blockIdx.x == 128) return;
    const int tid = threadIdx.x;
    const int r = tid & 15, q = tid >> 4;
#pragma unroll 1
    for (int ph = 0; ph < 3; ph++) {
      if (ph) {
        float y256 = 0.f;
        if (ph == 2) {
          mbar_wait(bar_tile, 0);
          if (tid == 0) TS(17);
          y256 = __ldcg(&g_spec[(size_t)256 * S_ + s0 + r]).x;
        }
        const float sg = ph == 1 ? -1.f : 1.f, sc = ph == 1 ? 0.5f : 1.f;
#pragma unroll 2
        for (int i = 0; i < 8; i++) {
          const int j = q + 16 * i;
          float2* pa = tile_at(tile, j, r);
          float2* pb = tile_at(tile, j == 0 ? 128 : 256 - j, r);
          const float2 A = *pa, B = *pb;
          const float2 P = make_float2(sc * (A.x + B.x), sc * (A.y - B.y)), M = make_float2(sc * (A.x - B.x), sc * (A.y + B.y));
          const float2 tw = twcs<512>(j);
          const float ts = sg * tw.y;
          const float2 T = make_float2(M.x * tw.x - M.y * ts, M.y * tw.x + M.x * ts);
          const float2 V = make_float2(-sg * T.y, sg * T.x);
          if (j) {
            *pa = make_float2(P.x + V.x, -sg * (P.y + V.y));
            *pb = make_float2(P.x - V.x, sg * (P.y - V.y));
          } else if (ph == 1) {
            g_spec[(size_t)256 * S_ + s0 + r] = make_float2(A.x - A.y, 0.f);
            *pa = make_float2(A.x + A.y, 0.f);
            *pb = cconj(B);
          } else {
            *pa = make_float2(A.x + y256, y256 - A.x);
            *pb = make_float2(2.f * B.x, 2.f * B.y);
          }
        }
      }
      if (ph == 1) {
        fence_async();
        mbar_arrive(bar_p1);
        gemm_part(smem, maps, b1, rt, sp);
        continue;
      }
      if (ph == 0) {
        uint32_t w[16];
        const uint32_t* xw = reinterpret_cast<const uint32_t*>(x + (size_t)(s0 + q) * D_);
#pragma unroll
        for (int n1 = 0; n1 < 16; n1++) w[n1] = __ldg(xw + 16 * n1 + r);
        if ((tid & 127) < 112) {
          const uint32_t* pw = reinterpret_cast<const uint32_t*>(w1 + (size_t)(rt * 32 + (tid >> 7) * 16) * F_ + sp * FC) + (tid & 127);
          float c0 = 0.f, c1 = 0.f;
#pragma unroll
          for (int k = 0; k < 16; k++) { const uint32_t ww = __ldg(pw + k * (F_ / 2)); c0 += bflo(ww); c1 += bfhi(ww); }
          g_cs[(sp * 32 + rt * 2 + (tid >> 7)) * 112 + (tid & 127)] = make_float2(c0, c1);
        }
        float sum = 0.f;
#pragma unroll
        for (int n1 = 0; n1 < 16; n1++) sum += bflo(w[n1]) + bfhi(w[n1]);
#pragma unroll
        for (int o = 1; o < 16; o <<= 1) sum += __shfl_xor_sync(0xffffffffu, sum, o);
        const float mean = sum * (1.0f / D_);
        float sq = 0.f;
#pragma unroll
        for (int n1 = 0; n1 < 16; n1++) {
          float a = bflo(w[n1]) - mean, c = bfhi(w[n1]) - mean;
          sq += a * a + c * c;
        }
#pragma unroll
        for (int o = 1; o < 16; o <<= 1) sq += __shfl_xor_sync(0xffffffffu, sq, o);
        const uint32_t nm2 = pack_bf16(-mean, -mean);
        float sd, rs;
        asm("sqrt.approx.f32 %0, %1;" : "=f"(sd) : "f"(bf16r(bf16r(sq * (1.0f / D_)) + 1e-5f)));
        asm("rcp.approx.f32 %0, %1;" : "=f"(rs) : "f"(bf16r(sd)));
        if (r == 0) g_stats[s0 + q] = make_float2(-bflo(nm2), rs);
#pragma unroll
        for (int n1 = 0; n1 < 16; n1++) {
          const uint32_t d = hadd2_bf16(w[n1], nm2);
          const uint32_t xn = pack_bf16(bflo(d) * rs, bfhi(d) * rs);
          *tile_at(tile, 16 * n1 + r, q) = make_float2(bflo(xn), bfhi(xn));
        }
      }
      named_bar(1, 256);
      {
        uint8_t* pa = reinterpret_cast<uint8_t*>(tile_at(tile, q, r));
        const uint8_t* pb = tile + q * 2048 + (r & 1) * 8;
#pragma unroll 1
        for (int p = 0; p < 2; p++) {
          float2 v[16];
#pragma unroll
          for (int i = 0; i < 16; i++)
            v[i] = *reinterpret_cast<const float2*>(p ? pb + i * 128 + ((((r >> 1) ^ i) & 7) << 4) : pa + i * 2048);
          dft16<-1>(v);
          if (p == 0) twiddle16(v, 8 * q);
          named_bar(1, 256);
          if (p && ph) {
#pragma unroll
            for (int i = 0; i < 16; i++) reinterpret_cast<uint32_t*>(tile)[r * SPITCH + q + 16 * i] = pack_bf16(v[O16(i)].x, -v[O16(i)].y);
          } else {
#pragma unroll
            for (int i = 0; i < 16; i++) *reinterpret_cast<float2*>(pa + i * 2048) = v[O16(i)];
          }
          named_bar(1, 256);
        }
      }
      if (tid == 0 && ph == 0) TS(10);
    }
    if (tid == 0) TS(16);
    {
      const int g = lane >> 2;
      const uint32_t* stile = reinterpret_cast<const uint32_t*>(tile);
      const uint32_t* xs = reinterpret_cast<const uint32_t*>(smem + 131072);
#pragma unroll 1
      for (int jq = 0; jq < NJOB; jq++) {
        const int cw = jq * 64 + 8 * warp + (lane & 3);
        mbar_wait(bar_g + 8 * jq, 0);
        const uint4* src = reinterpret_cast<const uint4*>(smem + jq * 32768) + tid;
        float o[8];
#pragma unroll
        for (int c = 0; c < 8; c++) o[c] = 0.f;
#pragma unroll
        for (int s = 0; s < 8; s++) {
          const uint4 v = src[s * 256];
          o[0] += bflo(v.x); o[1] += bfhi(v.x); o[2] += bflo(v.y); o[3] += bfhi(v.y);
          o[4] += bflo(v.z); o[5] += bfhi(v.z); o[6] += bflo(v.w); o[7] += bfhi(v.w);
        }
#pragma unroll
        for (int c = 0; c < 4; c++) {
          const int row = g + 8 * (c & 1), w = cw + 4 * (c >> 1);
          const uint32_t sw = stile[row * SPITCH + w];
          const uint32_t p = hadd2_bf16(pack_bf16(0.5f * o[2 * c], 0.5f * o[2 * c + 1]), xs[16 * SPITCH + w]);
          const float oa = bflo(p), ob = bfhi(p);
          const uint32_t gg = pack_bf16(__fdividef(oa, 1.0f + __expf(-oa)), __fdividef(ob, 1.0f + __expf(-ob)));
          const uint32_t sg = pack_bf16(bflo(sw) * bflo(gg), bfhi(sw) * bfhi(gg));
          reinterpret_cast<uint32_t*>(out)[(size_t)(s0 + row) * 256 + w] = hadd2_bf16(xs[row * SPITCH + w], sg);
        }
        if (tid == 0) TS(20 + jq);
      }
    }
  }
}

typedef CUresult (*EncodeFn)(CUtensorMap*, CUtensorMapDataType, cuuint32_t, void*, const cuuint64_t*, const cuuint64_t*,
                             const cuuint32_t*, const cuuint32_t*, CUtensorMapInterleave, CUtensorMapSwizzle,
                             CUtensorMapL2promotion, CUtensorMapFloatOOBfill);

}

extern "C" void kernel_launch(void* const* d_in, const int* in_sizes, int n_in, void* d_out, int out_size) {
  const __nv_bfloat16* x = (const __nv_bfloat16*)d_in[0];
  const __nv_bfloat16* wr = (const __nv_bfloat16*)d_in[1];
  const __nv_bfloat16* wi = (const __nv_bfloat16*)d_in[2];
  const __nv_bfloat16* w1 = (const __nv_bfloat16*)d_in[4];
  const __nv_bfloat16* b1 = (const __nv_bfloat16*)d_in[5];
  const __nv_bfloat16* w2 = (const __nv_bfloat16*)d_in[6];
  const __nv_bfloat16* b2 = (const __nv_bfloat16*)d_in[7];
  __nv_bfloat16* out = (__nv_bfloat16*)d_out;

  static EncodeFn enc = nullptr;
  static void* p_spec = nullptr;
  static void* p_wt = nullptr;
  if (!enc) {
    void* fn = nullptr;
    cudaDriverEntryPointQueryResult qr;
    cudaGetDriverEntryPoint("cuTensorMapEncodeTiled", &fn, cudaEnableDefault, &qr);
    enc = (EncodeFn)fn;
    cudaFuncSetAttribute(k_mega, cudaFuncAttributeMaxDynamicSharedMemorySize, SM_TOTAL);
    cudaGetSymbolAddress(&p_spec, g_spec);
    cudaGetSymbolAddress(&p_wt, g_wt);
  }
  Maps m;
  const cuuint32_t es[3] = {1, 1, 1};
  {
    cuuint64_t dims[2] = {(cuuint64_t)D_, (cuuint64_t)S_};
    cuuint64_t strides[1] = {(cuuint64_t)D_ * 2};
    cuuint32_t box[2] = {64, 128};
    enc(&m.x, CU_TENSOR_MAP_DATA_TYPE_BFLOAT16, 2, (void*)x, dims, strides, box, es, CU_TENSOR_MAP_INTERLEAVE_NONE,
        CU_TENSOR_MAP_SWIZZLE_128B, CU_TENSOR_MAP_L2_PROMOTION_L2_128B, CU_TENSOR_MAP_FLOAT_OOB_FILL_NONE);
  }
  {
    cuuint64_t dims[3] = {32, 512, 56};
    cuuint64_t strides[2] = {(cuuint64_t)F_ * 2, 64};
    cuuint32_t box[3] = {32, 32, 7};
    enc(&m.w1, CU_TENSOR_MAP_DATA_TYPE_BFLOAT16, 3, (void*)w1, dims, strides, box, es, CU_TENSOR_MAP_INTERLEAVE_NONE,
        CU_TENSOR_MAP_SWIZZLE_64B, CU_TENSOR_MAP_L2_PROMOTION_L2_128B, CU_TENSOR_MAP_FLOAT_OOB_FILL_NONE);
  }
  {
    cuuint64_t dims[2] = {(cuuint64_t)D_, (cuuint64_t)F_};
    cuuint64_t strides[1] = {(cuuint64_t)D_ * 2};
    cuuint32_t box[2] = {64, 112};
    enc(&m.w2, CU_TENSOR_MAP_DATA_TYPE_BFLOAT16, 2, (void*)w2, dims, strides, box, es, CU_TENSOR_MAP_INTERLEAVE_NONE,
        CU_TENSOR_MAP_SWIZZLE_128B, CU_TENSOR_MAP_L2_PROMOTION_L2_128B, CU_TENSOR_MAP_FLOAT_OOB_FILL_NONE);
  }
  {
    cuuint64_t dims[2] = {(cuuint64_t)S_, 256};
    cuuint64_t strides[1] = {(cuuint64_t)S_ * 8};
    cuuint32_t box[2] = {16, 256};
    enc(&m.spec, CU_TENSOR_MAP_DATA_TYPE_FLOAT64, 2, p_spec, dims, strides, box, es, CU_TENSOR_MAP_INTERLEAVE_NONE,
        CU_TENSOR_MAP_SWIZZLE_128B, CU_TENSOR_MAP_L2_PROMOTION_NONE, CU_TENSOR_MAP_FLOAT_OOB_FILL_NONE);
  }
  {
    cuuint64_t dims[2] = {(cuuint64_t)S_, 257};
    cuuint64_t strides[1] = {(cuuint64_t)S_ * 4};
    cuuint32_t box[2] = {16, 32};
    enc(&m.wt, CU_TENSOR_MAP_DATA_TYPE_UINT32, 2, p_wt, dims, strides, box, es, CU_TENSOR_MAP_INTERLEAVE_NONE,
        CU_TENSOR_MAP_SWIZZLE_64B, CU_TENSOR_MAP_L2_PROMOTION_NONE, CU_TENSOR_MAP_FLOAT_OOB_FILL_NONE);
  }
  k_mega<<<129, NTHREADS, SM_TOTAL>>>(x, wr, wi, w1, b1, b2, out, m);
}
```

```cpp
#include <cuda_runtime.h>
#include <cuda_bf16.h>
#include <cuda.h>
#include <stdint.h>

namespace {

constexpr int S_ = 2048, D_ = 512, F_ = 1792, DF_ = 257;
constexpr int FC = 224;
constexpr int NJOB = 4;

__device__ __align__(1024) float2 g_spec[257 * 2048];
__device__ __align__(1024) uint32_t g_wt[257 * 2048];
__device__ uint4 g_part[16 * NJOB * 8 * 8 * 256];
__device__ float2 g_cs[8 * 32 * 112];
__device__ float2 g_stats[2048];
__device__ unsigned g_bar[2];
__device__ unsigned g_flag[16 * NJOB * 8];
#define TS(i)

__device__ __forceinline__ uint32_t smem_u32(const void* p) { return (uint32_t)__cvta_generic_to_shared(p); }
__device__ __forceinline__ float bf16r(float x) { return __bfloat162float(__float2bfloat16_rn(x)); }
__device__ __forceinline__ float bflo(uint32_t w) { return __uint_as_float(w << 16); }
__device__ __forceinline__ float bfhi(uint32_t w) { return __uint_as_float(w & 0xffff0000u); }
__device__ __forceinline__ uint32_t pack_bf16(float lo, float hi) {
  uint32_t r;
  asm("cvt.rn.bf16x2.f32 %0, %1, %2;" : "=r"(r) : "f"(hi), "f"(lo));
  return r;
}
__device__ __forceinline__ uint32_t hadd2_bf16(uint32_t a, uint32_t b) {
  uint32_t r;
  asm("add.rn.bf16x2 %0, %1, %2;" : "=r"(r) : "r"(a), "r"(b));
  return r;
}
__device__ __forceinline__ void named_bar(int id, int n) { asm volatile("bar.sync %0, %1;" ::"r"(id), "r"(n) : "memory"); }
__device__ __forceinline__ void fence_async() { asm volatile("fence.proxy.async;" ::: "memory"); }

__device__ __forceinline__ void mbar_init(uint32_t bar, int cnt) { asm volatile("mbarrier.init.shared::cta.b64 [%0], %1;" ::"r"(bar), "r"(cnt) : "memory"); }
__device__ __forceinline__ void mbar_expect_tx(uint32_t bar, uint32_t bytes) { asm volatile("mbarrier.arrive.expect_tx.shared::cta.b64 _, [%0], %1;" ::"r"(bar), "r"(bytes) : "memory"); }
__device__ __forceinline__ void mbar_arrive(uint32_t bar) { asm volatile("mbarrier.arrive.shared::cta.b64 _, [%0];" ::"r"(bar) : "memory"); }
__device__ __forceinline__ bool mbar_try(uint32_t bar, uint32_t parity) {
  uint32_t ok;
  asm volatile("{\n.reg .pred p;\nmbarrier.try_wait.parity.shared::cta.b64 p, [%1], %2, %3;\nselp.u32 %0, 1, 0, p;\n}\n" : "=r"(ok) : "r"(bar), "r"(parity), "r"(20000u) : "memory");
  return ok != 0;
}
__device__ __forceinline__ void mbar_wait(uint32_t bar, uint32_t parity) {
  int it = 0;
  while (!mbar_try(bar, parity)) {
    if (++it > (1 << 22)) __trap();
  }
}
__device__ __forceinline__ void tma_load_3d(uint32_t dst, const CUtensorMap* map, int c0, int c1, int c2, uint32_t bar) {
  asm volatile("cp.async.bulk.tensor.3d.shared::cluster.global.mbarrier::complete_tx::bytes [%0], [%1, {%3, %4, %5}], [%2];"
               ::"r"(dst), "l"((uint64_t)map), "r"(bar), "r"(c0), "r"(c1), "r"(c2) : "memory");
}
__device__ __forceinline__ void tma_load_2d(uint32_t dst, const CUtensorMap* map, int c0, int c1, uint32_t bar) {
  asm volatile("cp.async.bulk.tensor.2d.shared::cluster.global.mbarrier::complete_tx::bytes [%0], [%1, {%3, %4}], [%2];"
               ::"r"(dst), "l"((uint64_t)map), "r"(bar), "r"(c0), "r"(c1) : "memory");
}
__device__ __forceinline__ void tma_store_2d(const CUtensorMap* map, int c0, int c1, uint32_t src) {
  asm volatile("cp.async.bulk.tensor.2d.global.shared::cta.bulk_group [%0, {%2, %3}], [%1];"
               ::"l"((uint64_t)map), "r"(src), "r"(c0), "r"(c1) : "memory");
}
__device__ __forceinline__ void tma_store_commit_wait() {
  asm volatile("cp.async.bulk.commit_group;" ::: "memory");
  asm volatile("cp.async.bulk.wait_group 0;" ::: "memory");
}
__device__ __forceinline__ void wgmma_fence() { asm volatile("wgmma.fence.sync.aligned;" ::: "memory"); }
__device__ __forceinline__ void wgmma_commit() { asm volatile("wgmma.commit_group.sync.aligned;" ::: "memory"); }
template <int N> __device__ __forceinline__ void wgmma_wait() { asm volatile("wgmma.wait_group.sync.aligned %0;" ::"n"(N) : "memory"); }
__device__ __forceinline__ uint64_t make_desc(uint32_t addr, uint32_t lbo_bytes, uint32_t sbo_bytes, uint32_t swz) {
  uint64_t d = 0;
  d |= (uint64_t)((addr & 0x3FFFF) >> 4);
  d |= (uint64_t)((lbo_bytes & 0x3FFFF) >> 4) << 16;
  d |= (uint64_t)((sbo_bytes & 0x3FFFF) >> 4) << 32;
  d |= (uint64_t)swz << 62;
  return d;
}
__device__ __forceinline__ unsigned ld_acquire(const unsigned* p) {
  unsigned v;
  asm volatile("ld.acquire.gpu.global.u32 %0, [%1];" : "=r"(v) : "l"(p) : "memory");
  return v;
}

__device__ __forceinline__ void wgmma_n224_ss(float (&d)[112], uint64_t da, uint64_t db, int scale_d) {
  asm volatile("{\n.reg .pred p;\nsetp.ne.b32 p, %114, 0;\n"
    "wgmma.mma_async.sync.aligned.m64n224k16.f32.bf16.bf16 {%0, %1, %2, %3, %4, %5, %6, %7, %8, %9, %10, %11, %12, %13, %14, %15, %16, %17, %18, %19, %20, %21, %22, %23, %24, %25, %26, %27, %28, %29, %30, %31, %32, %33, %34, %35, %36, %37, %38, %39, %40, %41, %42, %43, %44, %45, %46, %47, %48, %49, %50, %51, %52, %53, %54, %55, %56, %57, %58, %59, %60, %61, %62, %63, %64, %65, %66, %67, %68, %69, %70, %71, %72, %73, %74, %75, %76, %77, %78, %79, %80, %81, %82, %83, %84, %85, %86, %87, %88, %89, %90, %91, %92, %93, %94, %95, %96, %97, %98, %99, %100, %101, %102, %103, %104, %105, %106, %107, %108, %109, %110, %111}, %112, %113, p, 1, 1, 0, 1;\n}\n"
    : "+f"(d[0]), "+f"(d[1]), "+f"(d[2]), "+f"(d[3]), "+f"(d[4]), "+f"(d[5]), "+f"(d[6]), "+f"(d[7]), "+f"(d[8]), "+f"(d[9]), "+f"(d[10]), "+f"(d[11]), "+f"(d[12]), "+f"(d[13]), "+f"(d[14]), "+f"(d[15]), "+f"(d[16]), "+f"(d[17]), "+f"(d[18]), "+f"(d[19]), "+f"(d[20]), "+f"(d[21]), "+f"(d[22]), "+f"(d[23]), "+f"(d[24]), "+f"(d[25]), "+f"(d[26]), "+f"(d[27]), "+f"(d[28]), "+f"(d[29]), "+f"(d[30]), "+f"(d[31]), "+f"(d[32]), "+f"(d[33]), "+f"(d[34]), "+f"(d[35]), "+f"(d[36]), "+f"(d[37]), "+f"(d[38]), "+f"(d[39]), "+f"(d[40]), "+f"(d[41]), "+f"(d[42]), "+f"(d[43]), "+f"(d[44]), "+f"(d[45]), "+f"(d[46]), "+f"(d[47]), "+f"(d[48]), "+f"(d[49]), "+f"(d[50]), "+f"(d[51]), "+f"(d[52]), "+f"(d[53]), "+f"(d[54]), "+f"(d[55]), "+f"(d[56]), "+f"(d[57]), "+f"(d[58]), "+f"(d[59]), "+f"(d[60]), "+f"(d[61]), "+f"(d[62]), "+f"(d[63]), "+f"(d[64]), "+f"(d[65]), "+f"(d[66]), "+f"(d[67]), "+f"(d[68]), "+f"(d[69]), "+f"(d[70]), "+f"(d[71]), "+f"(d[72]), "+f"(d[73]), "+f"(d[74]), "+f"(d[75]), "+f"(d[76]), "+f"(d[77]), "+f"(d[78]), "+f"(d[79]), "+f"(d[80]), "+f"(d[81]), "+f"(d[82]), "+f"(d[83]), "+f"(d[84]), "+f"(d[85]), "+f"(d[86]), "+f"(d[87]), "+f"(d[88]), "+f"(d[89]), "+f"(d[90]), "+f"(d[91]), "+f"(d[92]), "+f"(d[93]), "+f"(d[94]), "+f"(d[95]), "+f"(d[96]), "+f"(d[97]), "+f"(d[98]), "+f"(d[99]), "+f"(d[100]), "+f"(d[101]), "+f"(d[102]), "+f"(d[103]), "+f"(d[104]), "+f"(d[105]), "+f"(d[106]), "+f"(d[107]), "+f"(d[108]), "+f"(d[109]), "+f"(d[110]), "+f"(d[111])
    : "l"(da), "l"(db), "r"(scale_d));
}
__device__ __forceinline__ void wgmma_n128_rs(float (&d)[64], uint32_t a0, uint32_t a1, uint32_t a2, uint32_t a3, uint64_t db, int scale_d) {
  asm volatile("{\n.reg .pred p;\nsetp.ne.b32 p, %69, 0;\n"
    "wgmma.mma_async.sync.aligned.m64n128k16.f32.bf16.bf16 {%0, %1, %2, %3, %4, %5, %6, %7, %8, %9, %10, %11, %12, %13, %14, %15, %16, %17, %18, %19, %20, %21, %22, %23, %24, %25, %26, %27, %28, %29, %30, %31, %32, %33, %34, %35, %36, %37, %38, %39, %40, %41, %42, %43, %44, %45, %46, %47, %48, %49, %50, %51, %52, %53, %54, %55, %56, %57, %58, %59, %60, %61, %62, %63}, {%64, %65, %66, %67}, %68, p, 1, 1, 1;\n}\n"
    : "+f"(d[0]), "+f"(d[1]), "+f"(d[2]), "+f"(d[3]), "+f"(d[4]), "+f"(d[5]), "+f"(d[6]), "+f"(d[7]), "+f"(d[8]), "+f"(d[9]), "+f"(d[10]), "+f"(d[11]), "+f"(d[12]), "+f"(d[13]), "+f"(d[14]), "+f"(d[15]), "+f"(d[16]), "+f"(d[17]), "+f"(d[18]), "+f"(d[19]), "+f"(d[20]), "+f"(d[21]), "+f"(d[22]), "+f"(d[23]), "+f"(d[24]), "+f"(d[25]), "+f"(d[26]), "+f"(d[27]), "+f"(d[28]), "+f"(d[29]), "+f"(d[30]), "+f"(d[31]), "+f"(d[32]), "+f"(d[33]), "+f"(d[34]), "+f"(d[35]), "+f"(d[36]), "+f"(d[37]), "+f"(d[38]), "+f"(d[39]), "+f"(d[40]), "+f"(d[41]), "+f"(d[42]), "+f"(d[43]), "+f"(d[44]), "+f"(d[45]), "+f"(d[46]), "+f"(d[47]), "+f"(d[48]), "+f"(d[49]), "+f"(d[50]), "+f"(d[51]), "+f"(d[52]), "+f"(d[53]), "+f"(d[54]), "+f"(d[55]), "+f"(d[56]), "+f"(d[57]), "+f"(d[58]), "+f"(d[59]), "+f"(d[60]), "+f"(d[61]), "+f"(d[62]), "+f"(d[63])
    : "r"(a0), "r"(a1), "r"(a2), "r"(a3), "l"(db), "r"(scale_d));
}

__device__ __forceinline__ float2 cadd(float2 a, float2 b) { return make_float2(a.x + b.x, a.y + b.y); }
__device__ __forceinline__ float2 csub(float2 a, float2 b) { return make_float2(a.x - b.x, a.y - b.y); }
__device__ __forceinline__ float2 cmul(float2 a, float2 b) { return make_float2(a.x * b.x - a.y * b.y, a.x * b.y + a.y * b.x); }
__device__ __forceinline__ float2 cconj(float2 a) { return make_float2(a.x, -a.y); }

template <int DIR> __device__ __forceinline__ void dft4(float2& a0, float2& a1, float2& a2, float2& a3) {
  float2 t0 = cadd(a0, a2), t1 = csub(a0, a2), t2 = cadd(a1, a3), t3 = csub(a1, a3);
  float2 t3r = DIR < 0 ? make_float2(t3.y, -t3.x) : make_float2(-t3.y, t3.x);
  a0 = cadd(t0, t2); a2 = csub(t0, t2); a1 = cadd(t1, t3r); a3 = csub(t1, t3r);
}
template <int DIR> __device__ __forceinline__ float2 mulw(float2 v, float c, float s) {
  return DIR < 0 ? make_float2(v.x * c + v.y * s, v.y * c - v.x * s) : make_float2(v.x * c - v.y * s, v.y * c + v.x * s);
}
template <int DIR> __device__ __forceinline__ float2 muli(float2 v) {
  return DIR < 0 ? make_float2(v.y, -v.x) : make_float2(-v.y, v.x);
}
#define O16(k) (4 * ((k) & 3) + ((k) >> 2))
#define O8(k) (2 * ((k) & 3) + ((k) >> 2))
template <int DIR> __device__ __forceinline__ void dft16(float2 (&v)[16]) {
  constexpr float C1 = 0.92387953251128674f, S1 = 0.38268343236508977f, R = 0.70710678118654752f;
#pragma unroll
  for (int n2 = 0; n2 < 4; n2++) dft4<DIR>(v[n2], v[4 + n2], v[8 + n2], v[12 + n2]);
  v[5] = mulw<DIR>(v[5], C1, S1);
  v[6] = mulw<DIR>(v[6], R, R);
  v[7] = mulw<DIR>(v[7], S1, C1);
  v[9] = mulw<DIR>(v[9], R, R);
  v[10] = muli<DIR>(v[10]);
  v[11] = mulw<DIR>(v[11], -R, R);
  v[13] = mulw<DIR>(v[13], S1, C1);
  v[14] = mulw<DIR>(v[14], -R, R);
  v[15] = mulw<DIR>(v[15], -C1, -S1);
#pragma unroll
  for (int k1 = 0; k1 < 4; k1++) dft4<DIR>(v[4 * k1], v[4 * k1 + 1], v[4 * k1 + 2], v[4 * k1 + 3]);
}
template <int DIR> __device__ __forceinline__ void dft8(float2 (&v)[8]) {
  constexpr float R = 0.70710678118654752f;
  dft4<DIR>(v[0], v[2], v[4], v[6]);
  dft4<DIR>(v[1], v[3], v[5], v[7]);
  v[3] = mulw<DIR>(v[3], R, R);
  v[5] = muli<DIR>(v[5]);
  v[7] = mulw<DIR>(v[7], -R, R);
#pragma unroll
  for (int k1 = 0; k1 < 4; k1++) {
    float2 a = v[2 * k1], b = v[2 * k1 + 1];
    v[2 * k1] = cadd(a, b); v[2 * k1 + 1] = csub(a, b);
  }
}
template <int N> __device__ __forceinline__ float2 twcs(int m) {
  m &= (N - 1);
  if (m >= N / 2) m -= N;
  float s, c;
  __sincosf((float)m * (6.283185307179586f / N), &s, &c);
  return make_float2(c, s);
}

__device__ __forceinline__ void twiddle16(float2 (&v)[16], int m) {
  const float2 w1 = twcs<2048>(m);
  float2 w = w1;
#pragma unroll
  for (int k = 1; k < 16; k++) {
    v[O16(k)] = mulw<-1>(v[O16(k)], w.x, w.y);
    if (k < 15) w = cmul(w, w1);
  }
}
__device__ __forceinline__ float2* tile_at(uint8_t* tile, int k, int r) {
  return reinterpret_cast<float2*>(tile + k * 128 + ((((r >> 1) ^ k) & 7) << 4) + (r & 1) * 8);
}
constexpr int SPITCH = 260;

constexpr int STEP = 45056;
constexpr int W1_STAGE = 14336;
constexpr int SM_FFT = 184 * 1024;
constexpr int SM_WT = SM_FFT + 32768;
constexpr int SM_BAR = SM_WT + 8192;
constexpr int SM_TAB = SM_BAR + 256;
constexpr int SM_TOTAL = SM_TAB + 1280;
constexpr int NTHREADS = 384;

__device__ __forceinline__ float gelu2(float x) {
  float u = x * (0.7978845608028654f + 0.035677408136300125f * x * x);
  float th;
  asm("tanh.approx.f32 %0, %1;" : "=f"(th) : "f"(u));
  return fmaf(x, th, x);
}
__device__ __forceinline__ unsigned grid_arrive(unsigned* cnt) {
  __threadfence();
  unsigned old = atomicAdd(cnt, 1u);
  return (old / 129u + 1u) * 129u;
}
__device__ __forceinline__ void grid_wait(const unsigned* cnt, unsigned target) {
  int it = 0;
  while ((int)(ld_acquire(cnt) - target) < 0) {
    if (++it > (1 << 22)) __trap();
  }
}
__device__ __forceinline__ uint32_t piece_off(int p) {
  if (p >= 12) p -= 12;
  const int s = (p * 11) >> 5;
  return (uint32_t)(s * STEP + (p - 3 * s) * W1_STAGE);
}

struct Maps { CUtensorMap x, w1, w2, spec, wt; };

__device__ __forceinline__ void issue_items(const uint8_t* smem, int first, int n) {
#pragma unroll 1
  for (int i = first; i < first + n; i++) {
    const uint4 a = *reinterpret_cast<const uint4*>(smem + SM_TAB + i * 32);
    const uint4 c = *reinterpret_cast<const uint4*>(smem + SM_TAB + i * 32 + 16);
    if (c.w) mbar_expect_tx(a.w, c.w);
    tma_load_3d(a.z, reinterpret_cast<const CUtensorMap*>((uint64_t)a.x | ((uint64_t)a.y << 32)), (int)c.x, (int)c.y, (int)c.z, a.w);
  }
}

__device__ __forceinline__ void gemm_part(uint8_t* smem, const Maps& maps, const __nv_bfloat16* __restrict__ b1, int rt, int sp) {
  const uint32_t sb = smem_u32(smem);
  const int tid = threadIdx.x, warp = tid >> 5, lane = tid & 31, wg = warp >> 2;
  const uint32_t bar_full1 = sb + SM_BAR, bar_full2 = sb + SM_BAR + 64;
  unsigned* relcnt = reinterpret_cast<unsigned*>(smem + SM_BAR + 128);
  const uint32_t bar_stats = sb + SM_BAR + 160, bar_st = sb + SM_BAR + 224;
  uint32_t ha[56];
      auto release = [&](int j) {
        __syncwarp();
        if (lane == 0) {
          __threadfence_block();
          if ((atomicAdd(&relcnt[j & 3], 1u) & 7u) == 7u) {
            __threadfence_block();
            issue_items(smem, 3 * j + 12, 3);
          }
        }
      };
      {
        float acc[112];
#pragma unroll
        for (int i = 0; i < 112; i++) acc[i] = 0.f;
        const uint64_t dA = make_desc(sb + __shfl_sync(0xffffffffu, wg, 0) * 8192, 16, 1024, 1), dB = make_desc(sb + 16384, 2048, 512, 2);
#pragma unroll 1
        for (int j = 0; j < 8; j++) {
          const uint32_t base = (j & 3) * STEP;
          mbar_wait(bar_full1 + 8 * (j & 3), j >> 2);
          if (tid == 0) TS(24 + j);
          wgmma_fence();
#pragma unroll
          for (int kk = 0; kk < 4; kk++)
            wgmma_n224_ss(acc, dA + ((base + kk * 32) >> 4), dB + ((base + (kk >> 1) * W1_STAGE + (kk & 1) * 1024) >> 4), 1);
          wgmma_commit();
          if (j > 0) {
            wgmma_wait<1>();
            release(j - 1);
          }
        }
        mbar_wait(bar_stats, 0);
        if (tid < 224) {
          float c0 = 0.f, c1 = 0.f;
          const float2* pc = g_cs + (sp * 32 + (tid & 1) * 16) * 112 + (tid >> 1);
#pragma unroll
          for (int i = 0; i < 16; i++) { const float2 c = __ldcg(pc + i * 112); c0 += c.x; c1 += c.y; }
          c0 += __shfl_xor_sync(0xffffffffu, c0, 1); c1 += __shfl_xor_sync(0xffffffffu, c1, 1);
          const uint32_t bw = __ldg(reinterpret_cast<const uint32_t*>(b1 + sp * FC) + (tid >> 1));
          reinterpret_cast<float4*>(smem + SM_WT)[tid >> 1] = make_float4(c0, c1, bflo(bw), bfhi(bw));
        }
        const int row = rt * 128 + warp * 16 + (lane >> 2);
        const float2 st0 = __ldcg(&g_stats[row]), st1 = __ldcg(&g_stats[row + 8]);
        wgmma_wait<0>();
        if (tid == 0) TS(2);
        named_bar(1, 256);
        if (tid == 0) {
          issue_items(smem, 33, 3);
        }
        if (tid == 0) TS(3);
        const float4* csb = reinterpret_cast<const float4*>(smem + SM_WT) + (lane & 3);
#pragma unroll
        for (int j = 0; j < 28; j++) {
          const float4 c = csb[j * 4];
          ha[2 * j] = pack_bf16(gelu2(fmaf(fmaf(-st0.x, c.x, acc[4 * j]), st0.y, c.z)), gelu2(fmaf(fmaf(-st0.x, c.y, acc[4 * j + 1]), st0.y, c.w)));
          ha[2 * j + 1] = pack_bf16(gelu2(fmaf(fmaf(-st1.x, c.x, acc[4 * j + 2]), st1.y, c.z)), gelu2(fmaf(fmaf(-st1.x, c.y, acc[4 * j + 3]), st1.y, c.w)));
        }
      }
      if (tid == 0) TS(4);
      if (wg == 1) named_bar(2, 256);
#pragma unroll 1
      for (int jq = 0; jq < NJOB; jq++) {
        float acc[64];
#pragma unroll
        for (int h = 0; h < 2; h++) {
          const uint32_t o0 = piece_off(4 * jq + 2 * h), o1 = piece_off(4 * jq + 2 * h + 1);
          const uint64_t dW = make_desc(sb + o0, o1 - o0, 1024, 1);
          mbar_wait(bar_full2 + 8 * (2 * jq + h), 0);
          wgmma_fence();
#pragma unroll
          for (int kk = 0; kk < 7; kk++) {
            const int kb = h * 7 + kk;
            wgmma_n128_rs(acc, ha[4 * kb], ha[4 * kb + 1], ha[4 * kb + 2], ha[4 * kb + 3], dW + kk * 128, kb > 0);
          }
          wgmma_commit();
        }
        if (jq == 0 && wg == 0) asm volatile("bar.arrive 2, 256;" ::: "memory");
        wgmma_wait<0>();
        if (jq == 0 && lane == 0) {
          __threadfence_block();
          if (atomicAdd(&relcnt[4], 1u) == 7u) {
            __threadfence_block();
            issue_items(smem, 36, 4);
          }
        }
        uint4* dstp = g_part + ((((size_t)rt * NJOB + jq) * 8 + warp) * 8 + sp) * 256 + lane;
#pragma unroll
        for (int i = 0; i < 8; i++)
          dstp[i * 32] = make_uint4(pack_bf16(acc[8 * i], acc[8 * i + 1]), pack_bf16(acc[8 * i + 2], acc[8 * i + 3]),
                                    pack_bf16(acc[8 * i + 4], acc[8 * i + 5]), pack_bf16(acc[8 * i + 6], acc[8 * i + 7]));
        __syncwarp();
        if (lane == 0) mbar_arrive(bar_st + 8 * jq);
        if (tid == 0) TS(5 + jq);
      }
}

__global__ void __launch_bounds__(NTHREADS, 1)
k_mega(const __nv_bfloat16* __restrict__ x, const __nv_bfloat16* __restrict__ wr, const __nv_bfloat16* __restrict__ wi,
       const __nv_bfloat16* __restrict__ w1, const __nv_bfloat16* __restrict__ b1, const __nv_bfloat16* __restrict__ b2, __nv_bfloat16* __restrict__ out,
       const __grid_constant__ Maps maps) {
  extern __shared__ __align__(1024) uint8_t smem[];
  const uint32_t sb = smem_u32(smem);
  const int rt = blockIdx.x >> 3, sp = blockIdx.x & 7;
  const int warp = threadIdx.x >> 5, lane = threadIdx.x & 31;
  const int s0 = blockIdx.x * 16;
  if (threadIdx.x == 0) TS(0);
  const uint32_t bar_full1 = sb + SM_BAR;
  const uint32_t bar_full2 = sb + SM_BAR + 64;
  unsigned* relcnt = reinterpret_cast<unsigned*>(smem + SM_BAR + 128);
  const uint32_t bar_stats = sb + SM_BAR + 160;
  const uint32_t bar_p1 = sb + SM_BAR + 168;
  const uint32_t bar_tile = sb + SM_BAR + 176;
  const uint32_t bar_st = sb + SM_BAR + 224;
  const uint32_t bar_g = sb + SM_BAR + 192;
  uint8_t* tile = smem + SM_FFT;

  if (threadIdx.x == 0) {
    for (int i = 0; i < 4; i++) mbar_init(bar_full1 + 8 * i, 1);
    for (int i = 0; i < 8; i++) mbar_init(bar_full2 + 8 * i, 2);
    mbar_init(bar_stats, 1); mbar_init(bar_p1, 256); mbar_init(bar_tile, 1);
    for (int i = 0; i < 4; i++) { mbar_init(bar_g + 8 * i, 1); mbar_init(bar_st + 8 * i, 8); }
    for (int i = 0; i < 5; i++) relcnt[i] = 0;
    asm volatile("fence.mbarrier_init.release.cluster;" ::: "memory");
  }
  if (warp == 1) {
#pragma unroll 1
    for (int i = lane; i < 40; i += 32) {
      uint64_t mp; uint32_t dst, bar, bytes; int c0, c1, c2;
      if (i < 24) {
        const int j = (i * 11) >> 5, part = i - 3 * j;
        bar = bar_full1 + 8 * (j & 3);
        bytes = part ? 0 : STEP;
        dst = sb + (j & 3) * STEP + (part ? 16384 + (part - 1) * W1_STAGE : 0);
        mp = (uint64_t)(part ? &maps.w1 : &maps.x);
        c0 = part ? 0 : j * 64; c1 = part ? j * 64 + (part - 1) * 32 : rt * 128; c2 = part ? sp * 7 : 0;
      } else {
        const int p = i - 24;
        bar = bar_full2 + 8 * (p >> 1);
        bytes = W1_STAGE;
        dst = sb + piece_off(p);
        mp = (uint64_t)&maps.w2;
        c0 = (p >> 2) * 128 + (p & 1) * 64; c1 = sp * FC + ((p >> 1) & 1) * 112; c2 = 0;
      }
      *reinterpret_cast<uint4*>(smem + SM_TAB + i * 32) = make_uint4((uint32_t)mp, (uint32_t)(mp >> 32), dst, bar);
      *reinterpret_cast<uint4*>(smem + SM_TAB + i * 32 + 16) = make_uint4(c0, c1, c2, bytes);
    }
  }
  __syncthreads();
  if (threadIdx.x == 32 && blockIdx.x < 128) issue_items(smem, 0, 12);

  if (warp >= 8) {
    const int t = threadIdx.x & 127;
    const bool extra = blockIdx.x == 128;
    if (!extra) {
      const uint32_t stg = (uint32_t)(SM_WT + (warp - 8) * 2048);
      if (t < 16) {
        const size_t o = (size_t)(s0 + t) * DF_ + 256;
        g_wt[(size_t)256 * S_ + s0 + t] = (uint32_t)__ldg(reinterpret_cast<const unsigned short*>(wr) + o) |
                                          ((uint32_t)__ldg(reinterpret_cast<const unsigned short*>(wi) + o) << 16);
      }
      uint32_t wv[2][16];
      {
        const unsigned short* pr = reinterpret_cast<const unsigned short*>(wr) + (size_t)s0 * DF_ + t;
        const unsigned short* pi = reinterpret_cast<const unsigned short*>(wi) + (size_t)s0 * DF_ + t;
#pragma unroll
        for (int u = 0; u < 32; u++)
          wv[u >> 4][u & 15] = (uint32_t)__ldg(pr + (u & 15) * DF_ + (u >> 4) * 128) | ((uint32_t)__ldg(pi + (u & 15) * DF_ + (u >> 4) * 128) << 16);
      }
#pragma unroll
      for (int rd = 0; rd < 2; rd++) {
        if (rd && lane == 0) asm volatile("cp.async.bulk.wait_group.read 0;" ::: "memory");
        __syncwarp();
#pragma unroll
        for (int c = 0; c < 4; c++)
          *reinterpret_cast<uint4*>(smem + stg + lane * 64 + ((c ^ ((lane >> 1) & 3)) << 4)) =
              make_uint4(wv[rd][4 * c], wv[rd][4 * c + 1], wv[rd][4 * c + 2], wv[rd][4 * c + 3]);
        fence_async();
        __syncwarp();
        if (lane == 0) {
          tma_store_2d(&maps.wt, s0, rd * 128 + (warp - 8) * 32, sb + stg);
          asm volatile("cp.async.bulk.commit_group;" ::: "memory");
        }
      }
      if (lane == 0) { asm volatile("cp.async.bulk.wait_group 0;" ::: "memory"); __threadfence(); }
    }
    named_bar(3, 128);
    if (t == 0) {
      TS(11);
      if (!extra) {
        mbar_wait(bar_p1, 0);
        tma_store_2d(&maps.spec, s0, 0, sb + SM_FFT);
        tma_store_commit_wait();
      }
      TS(12);
      const unsigned target = grid_arrive(&g_bar[0]);
      grid_wait(&g_bar[0], target);
      mbar_arrive(bar_stats);
    }
    named_bar(3, 128);
    if (t == 0) TS(13);
    {
      float2* buf = reinterpret_cast<float2*>(tile);
      const int k1 = t >> 3, m2 = t & 7;
      const int c0 = extra ? 256 : blockIdx.x * 2, nc = extra ? 1 : 2;
      float2 vn[16];
      uint32_t wn[16];
#pragma unroll 1
      for (int c = -1; c < nc; c++) {
        uint32_t wq[16];
        if (c >= 0) {
#pragma unroll
          for (int i = 0; i < 16; i++) { buf[128 * i + t] = vn[i]; wq[i] = wn[i]; }
        }
        if (c + 1 < nc) {
#pragma unroll
          for (int i = 0; i < 16; i++) {
            vn[i] = __ldcg(g_spec + (size_t)(c0 + c + 1) * S_ + 128 * i + t);
            wn[i] = __ldcg(g_wt + (size_t)(c0 + c + 1) * S_ + 128 * i + t);
          }
        }
        if (c < 0) continue;
#pragma unroll 1
        for (int it = 0; it < 2; it++) {
#pragma unroll 1
          for (int p = 0; p < 2; p++) {
            const float2* in = buf + (p ? k1 * 136 + m2 : t);
            const int is = p ? 8 : 128;
            float2 v[16];
#pragma unroll
            for (int i = 0; i < 16; i++) v[i] = in[i * is];
            dft16<-1>(v);
            twiddle16(v, p ? 16 * m2 : t);
            named_bar(3, 128);
            float2* o = buf + (p ? k1 * 9 + m2 : t);
            const int os = p ? 144 : 136;
#pragma unroll
            for (int kk = 0; kk < 16; kk++) o[kk * os] = v[O16(kk)];
            named_bar(3, 128);
          }
          float2 e[2][8];
#pragma unroll
          for (int m = 0; m < 8; m++) { e[0][m] = buf[t * 9 + m]; e[1][m] = buf[(t + 128) * 9 + m]; }
          dft8<-1>(e[0]);
          dft8<-1>(e[1]);
          named_bar(3, 128);
          if (it == 0) {
            constexpr float SC = 1.0f / (2048.0f * 512.0f);
#pragma unroll
            for (int i = 0; i < 16; i++)
              buf[128 * i + t] = cconj(cmul(e[i & 1][O8(i >> 1)], make_float2(bflo(wq[i]) * SC, bfhi(wq[i]) * SC)));
          } else {
            float2* col = g_spec + (size_t)(c0 + c) * S_ + t;
#pragma unroll
            for (int i = 0; i < 16; i++) col[128 * i] = cconj(e[i & 1][O8(i >> 1)]);
          }
        }
      }
    }
    named_bar(3, 128);
    if (warp == 9 && lane < 8 && !extra) {
#pragma unroll 1
      for (int jq = 0; jq < NJOB; jq++) {
        mbar_wait(bar_st + 8 * jq, 0);
        __threadfence();
        atomicAdd(&g_flag[(rt * NJOB + jq) * 8 + lane], 1u);
      }
    }
    if (t == 64 && !extra) {
        mbar_wait(bar_st + 24, 0);
#pragma unroll 1
        for (int jq = 0; jq < NJOB; jq++) {
          unsigned* fl = &g_flag[(rt * NJOB + jq) * 8 + sp];
          int it = 0;
          while (ld_acquire(fl) < 8u) {
            if (++it > (1 << 22)) __trap();
          }
          *fl = 0u;
          fence_async();
          mbar_expect_tx(bar_g + 8 * jq, jq ? 32768 : 32768 + 17 * 1024);
          if (jq == 0) {
#pragma unroll 1
            for (int i = 0; i < 17; i++)
              asm volatile("cp.async.bulk.shared::cluster.global.mbarrier::complete_tx::bytes [%0], [%1], %2, [%3];"
                           ::"r"(sb + 131072 + i * SPITCH * 4), "l"(i < 16 ? x + (size_t)(s0 + i) * D_ : b2), "r"(1024), "r"(bar_g) : "memory");
          }
          asm volatile("cp.async.bulk.shared::cluster.global.mbarrier::complete_tx::bytes [%0], [%1], %2, [%3];"
                       ::"r"(sb + jq * 32768), "l"(g_part + (((size_t)rt * NJOB + jq) * 8 + sp) * 8 * 256), "r"(32768), "r"(bar_g + 8 * jq) : "memory");
        }
    }
    if (t == 0) {
      TS(14);
      const unsigned target = grid_arrive(&g_bar[1]);
      if (!extra) {
        grid_wait(&g_bar[1], target);
        TS(15);
        fence_async();
        mbar_expect_tx(bar_tile, 32768);
        tma_load_2d(sb + SM_FFT, &maps.spec, s0, 0, bar_tile);
      }
    }
  } else {
    if (blockIdx.x == 128) return;
    const int tid = threadIdx.x;
    const int r = tid & 15, q = tid >> 4;
#pragma unroll 1
    for (int ph = 0; ph < 3; ph++) {
      if (ph) {
        float y256 = 0.f;
        if (ph == 2) {
          mbar_wait(bar_tile, 0);
          if (tid == 0) TS(17);
          y256 = __ldcg(&g_spec[(size_t)256 * S_ + s0 + r]).x;
        }
        const float sg = ph == 1 ? -1.f : 1.f, sc = ph == 1 ? 0.5f : 1.f;
#pragma unroll 2
        for (int i = 0; i < 8; i++) {
          const int j = q + 16 * i;
          float2* pa = tile_at(tile, j, r);
          float2* pb = tile_at(tile, j == 0 ? 128 : 256 - j, r);
          const float2 A = *pa, B = *pb;
          const float2 P = make_float2(sc * (A.x + B.x), sc * (A.y - B.y)), M = make_float2(sc * (A.x - B.x), sc * (A.y + B.y));
          const float2 tw = twcs<512>(j);
          const float ts = sg * tw.y;
          const float2 T = make_float2(M.x * tw.x - M.y * ts, M.y * tw.x + M.x * ts);
          const float2 V = make_float2(-sg * T.y, sg * T.x);
          if (j) {
            *pa = make_float2(P.x + V.x, -sg * (P.y + V.y));
            *pb = make_float2(P.x - V.x, sg * (P.y - V.y));
          } else if (ph == 1) {
            g_spec[(size_t)256 * S_ + s0 + r] = make_float2(A.x - A.y, 0.f);
            *pa = make_float2(A.x + A.y, 0.f);
            *pb = cconj(B);
          } else {
            *pa = make_float2(A.x + y256, y256 - A.x);
            *pb = make_float2(2.f * B.x, 2.f * B.y);
          }
        }
      }
      if (ph == 1) {
        fence_async();
        mbar_arrive(bar_p1);
        gemm_part(smem, maps, b1, rt, sp);
        continue;
      }
      if (ph == 0) {
        uint32_t w[16];
        const uint32_t* xw = reinterpret_cast<const uint32_t*>(x + (size_t)(s0 + q) * D_);
#pragma unroll
        for (int n1 = 0; n1 < 16; n1++) w[n1] = __ldg(xw + 16 * n1 + r);
        if ((tid & 127) < 112) {
          const uint32_t* pw = reinterpret_cast<const uint32_t*>(w1 + (size_t)(rt * 32 + (tid >> 7) * 16) * F_ + sp * FC) + (tid & 127);
          float c0 = 0.f, c1 = 0.f;
#pragma unroll
          for (int k = 0; k < 16; k++) { const uint32_t ww = __ldg(pw + k * (F_ / 2)); c0 += bflo(ww); c1 += bfhi(ww); }
          g_cs[(sp * 32 + rt * 2 + (tid >> 7)) * 112 + (tid & 127)] = make_float2(c0, c1);
        }
        float sum = 0.f;
#pragma unroll
        for (int n1 = 0; n1 < 16; n1++) sum += bflo(w[n1]) + bfhi(w[n1]);
#pragma unroll
        for (int o = 1; o < 16; o <<= 1) sum += __shfl_xor_sync(0xffffffffu, sum, o);
        const float mean = sum * (1.0f / D_);
        float sq = 0.f;
#pragma unroll
        for (int n1 = 0; n1 < 16; n1++) {
          float a = bflo(w[n1]) - mean, c = bfhi(w[n1]) - mean;
          sq += a * a + c * c;
        }
#pragma unroll
        for (int o = 1; o < 16; o <<= 1) sq += __shfl_xor_sync(0xffffffffu, sq, o);
        const uint32_t nm2 = pack_bf16(-mean, -mean);
        float sd, rs;
        asm("sqrt.approx.f32 %0, %1;" : "=f"(sd) : "f"(bf16r(bf16r(sq * (1.0f / D_)) + 1e-5f)));
        asm("rcp.approx.f32 %0, %1;" : "=f"(rs) : "f"(bf16r(sd)));
        if (r == 0) g_stats[s0 + q] = make_float2(-bflo(nm2), rs);
#pragma unroll
        for (int n1 = 0; n1 < 16; n1++) {
          const uint32_t d = hadd2_bf16(w[n1], nm2);
          const uint32_t xn = pack_bf16(bflo(d) * rs, bfhi(d) * rs);
          *tile_at(tile, 16 * n1 + r, q) = make_float2(bflo(xn), bfhi(xn));
        }
      }
      named_bar(1, 256);
      {
        uint8_t* pa = reinterpret_cast<uint8_t*>(tile_at(tile, q, r));
        const uint8_t* pb = tile + q * 2048 + (r & 1) * 8;
#pragma unroll 1
        for (int p = 0; p < 2; p++) {
          float2 v[16];
#pragma unroll
          for (int i = 0; i < 16; i++)
            v[i] = *reinterpret_cast<const float2*>(p ? pb + i * 128 + ((((r >> 1) ^ i) & 7) << 4) : pa + i * 2048);
          dft16<-1>(v);
          if (p == 0) twiddle16(v, 8 * q);
          named_bar(1, 256);
          if (p && ph) {
#pragma unroll
            for (int i = 0; i < 16; i++) reinterpret_cast<uint32_t*>(tile)[r * SPITCH + q + 16 * i] = pack_bf16(v[O16(i)].x, -v[O16(i)].y);
          } else {
#pragma unroll
            for (int i = 0; i < 16; i++) *reinterpret_cast<float2*>(pa + i * 2048) = v[O16(i)];
          }
          named_bar(1, 256);
        }
      }
      if (tid == 0 && ph == 0) TS(10);
    }
    if (tid == 0) TS(16);
    {
      const int g = lane >> 2;
      const uint32_t* stile = reinterpret_cast<const uint32_t*>(tile);
      const uint32_t* xs = reinterpret_cast<const uint32_t*>(smem + 131072);
#pragma unroll 1
      for (int jq = 0; jq < NJOB; jq++) {
        const int cw = jq * 64 + 8 * warp + (lane & 3);
        mbar_wait(bar_g + 8 * jq, 0);
        const uint4* src = reinterpret_cast<const uint4*>(smem + jq * 32768) + tid;
        float o[8];
#pragma unroll
        for (int c = 0; c < 8; c++) o[c] = 0.f;
#pragma unroll
        for (int s = 0; s < 8; s++) {
          const uint4 v = src[s * 256];
          o[0] += bflo(v.x); o[1] += bfhi(v.x); o[2] += bflo(v.y); o[3] += bfhi(v.y);
          o[4] += bflo(v.z); o[5] += bfhi(v.z); o[6] += bflo(v.w); o[7] += bfhi(v.w);
        }
#pragma unroll
        for (int c = 0; c < 4; c++) {
          const int row = g + 8 * (c & 1), w = cw + 4 * (c >> 1);
          const uint32_t sw = stile[row * SPITCH + w];
          const uint32_t p = hadd2_bf16(pack_bf16(0.5f * o[2 * c], 0.5f * o[2 * c + 1]), xs[16 * SPITCH + w]);
          const float oa = bflo(p), ob = bfhi(p);
          const uint32_t gg = pack_bf16(__fdividef(oa, 1.0f + __expf(-oa)), __fdividef(ob, 1.0f + __expf(-ob)));
          const uint32_t sg = pack_bf16(bflo(sw) * bflo(gg), bfhi(sw) * bfhi(gg));
          reinterpret_cast<uint32_t*>(out)[(size_t)(s0 + row) * 256 + w] = hadd2_bf16(xs[row * SPITCH + w], sg);
        }
        if (tid == 0) TS(20 + jq);
      }
    }
  }
}

typedef CUresult (*EncodeFn)(CUtensorMap*, CUtensorMapDataType, cuuint32_t, void*, const cuuint64_t*, const cuuint64_t*,
                             const cuuint32_t*, const cuuint32_t*, CUtensorMapInterleave, CUtensorMapSwizzle,
                             CUtensorMapL2promotion, CUtensorMapFloatOOBfill);

}

extern "C" void kernel_launch(void* const* d_in, const int* in_sizes, int n_in, void* d_out, int out_size) {
  const __nv_bfloat16* x = (const __nv_bfloat16*)d_in[0];
  const __nv_bfloat16* wr = (const __nv_bfloat16*)d_in[1];
  const __nv_bfloat16* wi = (const __nv_bfloat16*)d_in[2];
  const __nv_bfloat16* w1 = (const __nv_bfloat16*)d_in[4];
  const __nv_bfloat16* b1 = (const __nv_bfloat16*)d_in[5];
  const __nv_bfloat16* w2 = (const __nv_bfloat16*)d_in[6];
  const __nv_bfloat16* b2 = (const __nv_bfloat16*)d_in[7];
  __nv_bfloat16* out = (__nv_bfloat16*)d_out;

  static EncodeFn enc = nullptr;
  static void* p_spec = nullptr;
  static void* p_wt = nullptr;
  if (!enc) {
    void* fn = nullptr;
    cudaDriverEntryPointQueryResult qr;
    cudaGetDriverEntryPoint("cuTensorMapEncodeTiled", &fn, cudaEnableDefault, &qr);
    enc = (EncodeFn)fn;
    cudaFuncSetAttribute(k_mega, cudaFuncAttributeMaxDynamicSharedMemorySize, SM_TOTAL);
    cudaGetSymbolAddress(&p_spec, g_spec);
    cudaGetSymbolAddress(&p_wt, g_wt);
  }
  Maps m;
  const cuuint32_t es[3] = {1, 1, 1};
  {
    cuuint64_t dims[3] = {(cuuint64_t)D_, (cuuint64_t)S_, 1};
    cuuint64_t strides[2] = {(cuuint64_t)D_ * 2, (cuuint64_t)D_ * 2 * S_};
    cuuint32_t box[3] = {64, 128, 1};
    enc(&m.x, CU_TENSOR_MAP_DATA_TYPE_BFLOAT16, 3, (void*)x, dims, strides, box, es, CU_TENSOR_MAP_INTERLEAVE_NONE,
        CU_TENSOR_MAP_SWIZZLE_128B, CU_TENSOR_MAP_L2_PROMOTION_L2_128B, CU_TENSOR_MAP_FLOAT_OOB_FILL_NONE);
  }
  {
    cuuint64_t dims[3] = {32, 512, 56};
    cuuint64_t strides[2] = {(cuuint64_t)F_ * 2, 64};
    cuuint32_t box[3] = {32, 32, 7};
    enc(&m.w1, CU_TENSOR_MAP_DATA_TYPE_BFLOAT16, 3, (void*)w1, dims, strides, box, es, CU_TENSOR_MAP_INTERLEAVE_NONE,
        CU_TENSOR_MAP_SWIZZLE_64B, CU_TENSOR_MAP_L2_PROMOTION_L2_128B, CU_TENSOR_MAP_FLOAT_OOB_FILL_NONE);
  }
  {
    cuuint64_t dims[3] = {(cuuint64_t)D_, (cuuint64_t)F_, 1};
    cuuint64_t strides[2] = {(cuuint64_t)D_ * 2, (cuuint64_t)D_ * 2 * F_};
    cuuint32_t box[3] = {64, 112, 1};
    enc(&m.w2, CU_TENSOR_MAP_DATA_TYPE_BFLOAT16, 3, (void*)w2, dims, strides, box, es, CU_TENSOR_MAP_INTERLEAVE_NONE,
        CU_TENSOR_MAP_SWIZZLE_128B, CU_TENSOR_MAP_L2_PROMOTION_L2_128B, CU_TENSOR_MAP_FLOAT_OOB_FILL_NONE);
  }
  {
    cuuint64_t dims[2] = {(cuuint64_t)S_, 256};
    cuuint64_t strides[1] = {(cuuint64_t)S_ * 8};
    cuuint32_t box[2] = {16, 256};
    enc(&m.spec, CU_TENSOR_MAP_DATA_TYPE_FLOAT64, 2, p_spec, dims, strides, box, es, CU_TENSOR_MAP_INTERLEAVE_NONE,
        CU_TENSOR_MAP_SWIZZLE_128B, CU_TENSOR_MAP_L2_PROMOTION_NONE, CU_TENSOR_MAP_FLOAT_OOB_FILL_NONE);
  }
  {
    cuuint64_t dims[2] = {(cuuint64_t)S_, 257};
    cuuint64_t strides[1] = {(cuuint64_t)S_ * 4};
    cuuint32_t box[2] = {16, 32};
    enc(&m.wt, CU_TENSOR_MAP_DATA_TYPE_UINT32, 2, p_wt, dims, strides, box, es, CU_TENSOR_MAP_INTERLEAVE_NONE,
        CU_TENSOR_MAP_SWIZZLE_64B, CU_TENSOR_MAP_L2_PROMOTION_NONE, CU_TENSOR_MAP_FLOAT_OOB_FILL_NONE);
  }
  k_mega<<<129, NTHREADS, SM_TOTAL>>>(x, wr, wi, w1, b1, b2, out, m);
}
```

```cpp
#include <cuda_runtime.h>
#include <cuda_bf16.h>
#include <cuda.h>
#include <stdint.h>

namespace {

constexpr int S_ = 2048, D_ = 512, F_ = 1792, DF_ = 257;
constexpr int FC = 224;
constexpr int NJOB = 4;

__device__ __align__(1024) float2 g_spec[257 * 2048];
__device__ __align__(1024) uint32_t g_wt[257 * 2048];
__device__ uint4 g_part[16 * NJOB * 8 * 8 * 256];
__device__ float2 g_cs[8 * 32 * 112];
__device__ float2 g_stats[2048];
__device__ unsigned g_bar[2];
__device__ unsigned g_flag[16 * NJOB * 8];
#define TS(i)

__device__ __forceinline__ uint32_t smem_u32(const void* p) { return (uint32_t)__cvta_generic_to_shared(p); }
__device__ __forceinline__ float bf16r(float x) { return __bfloat162float(__float2bfloat16_rn(x)); }
__device__ __forceinline__ float bflo(uint32_t w) { return __uint_as_float(w << 16); }
__device__ __forceinline__ float bfhi(uint32_t w) { return __uint_as_float(w & 0xffff0000u); }
__device__ __forceinline__ uint32_t pack_bf16(float lo, float hi) {
  uint32_t r;
  asm("cvt.rn.bf16x2.f32 %0, %1, %2;" : "=r"(r) : "f"(hi), "f"(lo));
  return r;
}
__device__ __forceinline__ uint32_t hadd2_bf16(uint32_t a, uint32_t b) {
  uint32_t r;
  asm("add.rn.bf16x2 %0, %1, %2;" : "=r"(r) : "r"(a), "r"(b));
  return r;
}
__device__ __forceinline__ void named_bar(int id, int n) { asm volatile("bar.sync %0, %1;" ::"r"(id), "r"(n) : "memory"); }
__device__ __forceinline__ void fence_async() { asm volatile("fence.proxy.async;" ::: "memory"); }

__device__ __forceinline__ void mbar_init(uint32_t bar, int cnt) { asm volatile("mbarrier.init.shared::cta.b64 [%0], %1;" ::"r"(bar), "r"(cnt) : "memory"); }
__device__ __forceinline__ void mbar_expect_tx(uint32_t bar, uint32_t bytes) { asm volatile("mbarrier.arrive.expect_tx.shared::cta.b64 _, [%0], %1;" ::"r"(bar), "r"(bytes) : "memory"); }
__device__ __forceinline__ void mbar_arrive(uint32_t bar) { asm volatile("mbarrier.arrive.shared::cta.b64 _, [%0];" ::"r"(bar) : "memory"); }
__device__ __forceinline__ bool mbar_try(uint32_t bar, uint32_t parity) {
  uint32_t ok;
  asm volatile("{\n.reg .pred p;\nmbarrier.try_wait.parity.shared::cta.b64 p, [%1], %2, %3;\nselp.u32 %0, 1, 0, p;\n}\n" : "=r"(ok) : "r"(bar), "r"(parity), "r"(20000u) : "memory");
  return ok != 0;
}
__device__ __forceinline__ void mbar_wait(uint32_t bar, uint32_t parity) {
  int it = 0;
  while (!mbar_try(bar, parity)) {
    if (++it > (1 << 22)) __trap();
  }
}
__device__ __forceinline__ void tma_load_3d(uint32_t dst, const CUtensorMap* map, int c0, int c1, int c2, uint32_t bar) {
  asm volatile("cp.async.bulk.tensor.3d.shared::cluster.global.mbarrier::complete_tx::bytes [%0], [%1, {%3, %4, %5}], [%2];"
               ::"r"(dst), "l"((uint64_t)map), "r"(bar), "r"(c0), "r"(c1), "r"(c2) : "memory");
}
__device__ __forceinline__ void tma_load_2d(uint32_t dst, const CUtensorMap* map, int c0, int c1, uint32_t bar) {
  asm volatile("cp.async.bulk.tensor.2d.shared::cluster.global.mbarrier::complete_tx::bytes [%0], [%1, {%3, %4}], [%2];"
               ::"r"(dst), "l"((uint64_t)map), "r"(bar), "r"(c0), "r"(c1) : "memory");
}
__device__ __forceinline__ void tma_store_2d(const CUtensorMap* map, int c0, int c1, uint32_t src) {
  asm volatile("cp.async.bulk.tensor.2d.global.shared::cta.bulk_group [%0, {%2, %3}], [%1];"
               ::"l"((uint64_t)map), "r"(src), "r"(c0), "r"(c1) : "memory");
}
__device__ __forceinline__ void tma_store_commit_wait() {
  asm volatile("cp.async.bulk.commit_group;" ::: "memory");
  asm volatile("cp.async.bulk.wait_group 0;" ::: "memory");
}
__device__ __forceinline__ void wgmma_fence() { asm volatile("wgmma.fence.sync.aligned;" ::: "memory"); }
__device__ __forceinline__ void wgmma_commit() { asm volatile("wgmma.commit_group.sync.aligned;" ::: "memory"); }
template <int N> __device__ __forceinline__ void wgmma_wait() { asm volatile("wgmma.wait_group.sync.aligned %0;" ::"n"(N) : "memory"); }
__device__ __forceinline__ uint64_t make_desc(uint32_t addr, uint32_t lbo_bytes, uint32_t sbo_bytes, uint32_t swz) {
  uint64_t d = 0;
  d |= (uint64_t)((addr & 0x3FFFF) >> 4);
  d |= (uint64_t)((lbo_bytes & 0x3FFFF) >> 4) << 16;
  d |= (uint64_t)((sbo_bytes & 0x3FFFF) >> 4) << 32;
  d |= (uint64_t)swz << 62;
  return d;
}
__device__ __forceinline__ unsigned ld_acquire(const unsigned* p) {
  unsigned v;
  asm volatile("ld.acquire.gpu.global.u32 %0, [%1];" : "=r"(v) : "l"(p) : "memory");
  return v;
}

__device__ __forceinline__ void wgmma_n224_ss(float (&d)[112], uint64_t da, uint64_t db, int scale_d) {
  asm volatile("{\n.reg .pred p;\nsetp.ne.b32 p, %114, 0;\n"
    "wgmma.mma_async.sync.aligned.m64n224k16.f32.bf16.bf16 {%0, %1, %2, %3, %4, %5, %6, %7, %8, %9, %10, %11, %12, %13, %14, %15, %16, %17, %18, %19, %20, %21, %22, %23, %24, %25, %26, %27, %28, %29, %30, %31, %32, %33, %34, %35, %36, %37, %38, %39, %40, %41, %42, %43, %44, %45, %46, %47, %48, %49, %50, %51, %52, %53, %54, %55, %56, %57, %58, %59, %60, %61, %62, %63, %64, %65, %66, %67, %68, %69, %70, %71, %72, %73, %74, %75, %76, %77, %78, %79, %80, %81, %82, %83, %84, %85, %86, %87, %88, %89, %90, %91, %92, %93, %94, %95, %96, %97, %98, %99, %100, %101, %102, %103, %104, %105, %106, %107, %108, %109, %110, %111}, %112, %113, p, 1, 1, 0, 1;\n}\n"
    : "+f"(d[0]), "+f"(d[1]), "+f"(d[2]), "+f"(d[3]), "+f"(d[4]), "+f"(d[5]), "+f"(d[6]), "+f"(d[7]), "+f"(d[8]), "+f"(d[9]), "+f"(d[10]), "+f"(d[11]), "+f"(d[12]), "+f"(d[13]), "+f"(d[14]), "+f"(d[15]), "+f"(d[16]), "+f"(d[17]), "+f"(d[18]), "+f"(d[19]), "+f"(d[20]), "+f"(d[21]), "+f"(d[22]), "+f"(d[23]), "+f"(d[24]), "+f"(d[25]), "+f"(d[26]), "+f"(d[27]), "+f"(d[28]), "+f"(d[29]), "+f"(d[30]), "+f"(d[31]), "+f"(d[32]), "+f"(d[33]), "+f"(d[34]), "+f"(d[35]), "+f"(d[36]), "+f"(d[37]), "+f"(d[38]), "+f"(d[39]), "+f"(d[40]), "+f"(d[41]), "+f"(d[42]), "+f"(d[43]), "+f"(d[44]), "+f"(d[45]), "+f"(d[46]), "+f"(d[47]), "+f"(d[48]), "+f"(d[49]), "+f"(d[50]), "+f"(d[51]), "+f"(d[52]), "+f"(d[53]), "+f"(d[54]), "+f"(d[55]), "+f"(d[56]), "+f"(d[57]), "+f"(d[58]), "+f"(d[59]), "+f"(d[60]), "+f"(d[61]), "+f"(d[62]), "+f"(d[63]), "+f"(d[64]), "+f"(d[65]), "+f"(d[66]), "+f"(d[67]), "+f"(d[68]), "+f"(d[69]), "+f"(d[70]), "+f"(d[71]), "+f"(d[72]), "+f"(d[73]), "+f"(d[74]), "+f"(d[75]), "+f"(d[76]), "+f"(d[77]), "+f"(d[78]), "+f"(d[79]), "+f"(d[80]), "+f"(d[81]), "+f"(d[82]), "+f"(d[83]), "+f"(d[84]), "+f"(d[85]), "+f"(d[86]), "+f"(d[87]), "+f"(d[88]), "+f"(d[89]), "+f"(d[90]), "+f"(d[91]), "+f"(d[92]), "+f"(d[93]), "+f"(d[94]), "+f"(d[95]), "+f"(d[96]), "+f"(d[97]), "+f"(d[98]), "+f"(d[99]), "+f"(d[100]), "+f"(d[101]), "+f"(d[102]), "+f"(d[103]), "+f"(d[104]), "+f"(d[105]), "+f"(d[106]), "+f"(d[107]), "+f"(d[108]), "+f"(d[109]), "+f"(d[110]), "+f"(d[111])
    : "l"(da), "l"(db), "r"(scale_d));
}
__device__ __forceinline__ void wgmma_n128_rs(float (&d)[64], uint32_t a0, uint32_t a1, uint32_t a2, uint32_t a3, uint64_t db, int scale_d) {
  asm volatile("{\n.reg .pred p;\nsetp.ne.b32 p, %69, 0;\n"
    "wgmma.mma_async.sync.aligned.m64n128k16.f32.bf16.bf16 {%0, %1, %2, %3, %4, %5, %6, %7, %8, %9, %10, %11, %12, %13, %14, %15, %16, %17, %18, %19, %20, %21, %22, %23, %24, %25, %26, %27, %28, %29, %30, %31, %32, %33, %34, %35, %36, %37, %38, %39, %40, %41, %42, %43, %44, %45, %46, %47, %48, %49, %50, %51, %52, %53, %54, %55, %56, %57, %58, %59, %60, %61, %62, %63}, {%64, %65, %66, %67}, %68, p, 1, 1, 1;\n}\n"
    : "+f"(d[0]), "+f"(d[1]), "+f"(d[2]), "+f"(d[3]), "+f"(d[4]), "+f"(d[5]), "+f"(d[6]), "+f"(d[7]), "+f"(d[8]), "+f"(d[9]), "+f"(d[10]), "+f"(d[11]), "+f"(d[12]), "+f"(d[13]), "+f"(d[14]), "+f"(d[15]), "+f"(d[16]), "+f"(d[17]), "+f"(d[18]), "+f"(d[19]), "+f"(d[20]), "+f"(d[21]), "+f"(d[22]), "+f"(d[23]), "+f"(d[24]), "+f"(d[25]), "+f"(d[26]), "+f"(d[27]), "+f"(d[28]), "+f"(d[29]), "+f"(d[30]), "+f"(d[31]), "+f"(d[32]), "+f"(d[33]), "+f"(d[34]), "+f"(d[35]), "+f"(d[36]), "+f"(d[37]), "+f"(d[38]), "+f"(d[39]), "+f"(d[40]), "+f"(d[41]), "+f"(d[42]), "+f"(d[43]), "+f"(d[44]), "+f"(d[45]), "+f"(d[46]), "+f"(d[47]), "+f"(d[48]), "+f"(d[49]), "+f"(d[50]), "+f"(d[51]), "+f"(d[52]), "+f"(d[53]), "+f"(d[54]), "+f"(d[55]), "+f"(d[56]), "+f"(d[57]), "+f"(d[58]), "+f"(d[59]), "+f"(d[60]), "+f"(d[61]), "+f"(d[62]), "+f"(d[63])
    : "r"(a0), "r"(a1), "r"(a2), "r"(a3), "l"(db), "r"(scale_d));
}

__device__ __forceinline__ float2 cadd(float2 a, float2 b) { return make_float2(a.x + b.x, a.y + b.y); }
__device__ __forceinline__ float2 csub(float2 a, float2 b) { return make_float2(a.x - b.x, a.y - b.y); }
__device__ __forceinline__ float2 cmul(float2 a, float2 b) { return make_float2(a.x * b.x - a.y * b.y, a.x * b.y + a.y * b.x); }
__device__ __forceinline__ float2 cconj(float2 a) { return make_float2(a.x, -a.y); }

template <int DIR> __device__ __forceinline__ void dft4(float2& a0, float2& a1, float2& a2, float2& a3) {
  float2 t0 = cadd(a0, a2), t1 = csub(a0, a2), t2 = cadd(a1, a3), t3 = csub(a1, a3);
  float2 t3r = DIR < 0 ? make_float2(t3.y, -t3.x) : make_float2(-t3.y, t3.x);
  a0 = cadd(t0, t2); a2 = csub(t0, t2); a1 = cadd(t1, t3r); a3 = csub(t1, t3r);
}
template <int DIR> __device__ __forceinline__ float2 mulw(float2 v, float c, float s) {
  return DIR < 0 ? make_float2(v.x * c + v.y * s, v.y * c - v.x * s) : make_float2(v.x * c - v.y * s, v.y * c + v.x * s);
}
template <int DIR> __device__ __forceinline__ float2 muli(float2 v) {
  return DIR < 0 ? make_float2(v.y, -v.x) : make_float2(-v.y, v.x);
}
#define O16(k) (4 * ((k) & 3) + ((k) >> 2))
#define O8(k) (2 * ((k) & 3) + ((k) >> 2))
template <int DIR> __device__ __forceinline__ void dft16(float2 (&v)[16]) {
  constexpr float C1 = 0.92387953251128674f, S1 = 0.38268343236508977f, R = 0.70710678118654752f;
#pragma unroll
  for (int n2 = 0; n2 < 4; n2++) dft4<DIR>(v[n2], v[4 + n2], v[8 + n2], v[12 + n2]);
  v[5] = mulw<DIR>(v[5], C1, S1);
  v[6] = mulw<DIR>(v[6], R, R);
  v[7] = mulw<DIR>(v[7], S1, C1);
  v[9] = mulw<DIR>(v[9], R, R);
  v[10] = muli<DIR>(v[10]);
  v[11] = mulw<DIR>(v[11], -R, R);
  v[13] = mulw<DIR>(v[13], S1, C1);
  v[14] = mulw<DIR>(v[14], -R, R);
  v[15] = mulw<DIR>(v[15], -C1, -S1);
#pragma unroll
  for (int k1 = 0; k1 < 4; k1++) dft4<DIR>(v[4 * k1], v[4 * k1 + 1], v[4 * k1 + 2], v[4 * k1 + 3]);
}
template <int DIR> __device__ __forceinline__ void dft8(float2 (&v)[8]) {
  constexpr float R = 0.70710678118654752f;
  dft4<DIR>(v[0], v[2], v[4], v[6]);
  dft4<DIR>(v[1], v[3], v[5], v[7]);
  v[3] = mulw<DIR>(v[3], R, R);
  v[5] = muli<DIR>(v[5]);
  v[7] = mulw<DIR>(v[7], -R, R);
#pragma unroll
  for (int k1 = 0; k1 < 4; k1++) {
    float2 a = v[2 * k1], b = v[2 * k1 + 1];
    v[2 * k1] = cadd(a, b); v[2 * k1 + 1] = csub(a, b);
  }
}
template <int N> __device__ __forceinline__ float2 twcs(int m) {
  m &= (N - 1);
  if (m >= N / 2) m -= N;
  float s, c;
  __sincosf((float)m * (6.283185307179586f / N), &s, &c);
  return make_float2(c, s);
}

__device__ __forceinline__ void twiddle16(float2 (&v)[16], int m) {
  const float2 w1 = twcs<2048>(m);
  float2 w = w1;
#pragma unroll
  for (int k = 1; k < 16; k++) {
    v[O16(k)] = mulw<-1>(v[O16(k)], w.x, w.y);
    if (k < 15) w = cmul(w, w1);
  }
}
__device__ __forceinline__ float2* tile_at(uint8_t* tile, int k, int r) {
  return reinterpret_cast<float2*>(tile + k * 128 + ((((r >> 1) ^ k) & 7) << 4) + (r & 1) * 8);
}
constexpr int SPITCH = 260;

constexpr int STEP = 45056;
constexpr int W1_STAGE = 14336;
constexpr int SM_FFT = 184 * 1024;
constexpr int SM_WT = SM_FFT + 32768;
constexpr int SM_BAR = SM_WT + 8192;
constexpr int SM_TAB = SM_BAR + 256;
constexpr int SM_TOTAL = SM_TAB + 1280;
constexpr int NTHREADS = 384;

__device__ __forceinline__ float gelu2(float x) {
  float u = x * (0.7978845608028654f + 0.035677408136300125f * x * x);
  float th;
  asm("tanh.approx.f32 %0, %1;" : "=f"(th) : "f"(u));
  return fmaf(x, th, x);
}
__device__ __forceinline__ unsigned grid_arrive(unsigned* cnt) {
  __threadfence();
  unsigned old = atomicAdd(cnt, 1u);
  return (old / 129u + 1u) * 129u;
}
__device__ __forceinline__ void grid_wait(const unsigned* cnt, unsigned target) {
  int it = 0;
  while ((int)(ld_acquire(cnt) - target) < 0) {
    if (++it > (1 << 22)) __trap();
  }
}
__device__ __forceinline__ uint32_t piece_off(int p) {
  if (p >= 12) p -= 12;
  const int s = (p * 11) >> 5;
  return (uint32_t)(s * STEP + (p - 3 * s) * W1_STAGE);
}

struct Maps { CUtensorMap x, w1, w2, spec, wt; };

__device__ __forceinline__ void issue_items(const uint8_t* smem, int first, int n) {
#pragma unroll 1
  for (int i = first; i < first + n; i++) {
    const uint4 a = *reinterpret_cast<const uint4*>(smem + SM_TAB + i * 32);
    const uint4 c = *reinterpret_cast<const uint4*>(smem + SM_TAB + i * 32 + 16);
    if (c.w) mbar_expect_tx(a.w, c.w);
    tma_load_3d(a.z, reinterpret_cast<const CUtensorMap*>((uint64_t)a.x | ((uint64_t)a.y << 32)), (int)c.x, (int)c.y, (int)c.z, a.w);
  }
}

__device__ __forceinline__ void gemm_part(uint8_t* smem, const Maps& maps, const __nv_bfloat16* __restrict__ b1, int rt, int sp) {
  const uint32_t sb = smem_u32(smem);
  const int tid = threadIdx.x, warp = tid >> 5, lane = tid & 31, wg = warp >> 2;
  const uint32_t bar_full1 = sb + SM_BAR, bar_full2 = sb + SM_BAR + 64;
  unsigned* relcnt = reinterpret_cast<unsigned*>(smem + SM_BAR + 128);
  const uint32_t bar_stats = sb + SM_BAR + 160, bar_st = sb + SM_BAR + 224;
  uint32_t ha[56];
      auto release = [&](int j) {
        __syncwarp();
        if (lane == 0) {
          __threadfence_block();
          if ((atomicAdd(&relcnt[j & 3], 1u) & 7u) == 7u) {
            __threadfence_block();
            issue_items(smem, 3 * j + 12, 3);
          }
        }
      };
      {
        float acc[112];
#pragma unroll
        for (int i = 0; i < 112; i++) acc[i] = 0.f;
        const uint64_t dA = make_desc(sb + __shfl_sync(0xffffffffu, wg, 0) * 8192, 16, 1024, 1), dB = make_desc(sb + 16384, 2048, 512, 2);
#pragma unroll 1
        for (int j = 0; j < 8; j++) {
          const uint32_t base = (j & 3) * STEP;
          mbar_wait(bar_full1 + 8 * (j & 3), j >> 2);
          if (tid == 0) TS(24 + j);
          wgmma_fence();
#pragma unroll
          for (int kk = 0; kk < 4; kk++)
            wgmma_n224_ss(acc, dA + ((base + kk * 32) >> 4), dB + ((base + (kk >> 1) * W1_STAGE + (kk & 1) * 1024) >> 4), 1);
          wgmma_commit();
          if (j == 1 && lane == 0) {
            asm volatile("cp.async.bulk.wait_group 0;" ::: "memory");
            mbar_arrive(sb + SM_BAR + 168);
          }
          if (j > 0) {
            wgmma_wait<1>();
            release(j - 1);
          }
        }
        mbar_wait(bar_stats, 0);
        if (tid < 224) {
          float c0 = 0.f, c1 = 0.f;
          const float2* pc = g_cs + (sp * 32 + (tid & 1) * 16) * 112 + (tid >> 1);
#pragma unroll
          for (int i = 0; i < 16; i++) { const float2 c = __ldcg(pc + i * 112); c0 += c.x; c1 += c.y; }
          c0 += __shfl_xor_sync(0xffffffffu, c0, 1); c1 += __shfl_xor_sync(0xffffffffu, c1, 1);
          const uint32_t bw = __ldg(reinterpret_cast<const uint32_t*>(b1 + sp * FC) + (tid >> 1));
          reinterpret_cast<float4*>(smem + SM_WT)[tid >> 1] = make_float4(c0, c1, bflo(bw), bfhi(bw));
        }
        const int row = rt * 128 + warp * 16 + (lane >> 2);
        const float2 st0 = __ldcg(&g_stats[row]), st1 = __ldcg(&g_stats[row + 8]);
        wgmma_wait<0>();
        if (tid == 0) TS(2);
        named_bar(1, 256);
        if (tid == 0) {
          issue_items(smem, 33, 3);
        }
        if (tid == 0) TS(3);
        const float4* csb = reinterpret_cast<const float4*>(smem + SM_WT) + (lane & 3);
#pragma unroll
        for (int j = 0; j < 28; j++) {
          const float4 c = csb[j * 4];
          ha[2 * j] = pack_bf16(gelu2(fmaf(fmaf(-st0.x, c.x, acc[4 * j]), st0.y, c.z)), gelu2(fmaf(fmaf(-st0.x, c.y, acc[4 * j + 1]), st0.y, c.w)));
          ha[2 * j + 1] = pack_bf16(gelu2(fmaf(fmaf(-st1.x, c.x, acc[4 * j + 2]), st1.y, c.z)), gelu2(fmaf(fmaf(-st1.x, c.y, acc[4 * j + 3]), st1.y, c.w)));
        }
      }
      if (tid == 0) TS(4);
      if (wg == 1) named_bar(2, 256);
#pragma unroll 1
      for (int jq = 0; jq < NJOB; jq++) {
        float acc[64];
#pragma unroll
        for (int h = 0; h < 2; h++) {
          const uint32_t o0 = piece_off(4 * jq + 2 * h), o1 = piece_off(4 * jq + 2 * h + 1);
          const uint64_t dW = make_desc(sb + o0, o1 - o0, 1024, 1);
          mbar_wait(bar_full2 + 8 * (2 * jq + h), 0);
          wgmma_fence();
#pragma unroll
          for (int kk = 0; kk < 7; kk++) {
            const int kb = h * 7 + kk;
            wgmma_n128_rs(acc, ha[4 * kb], ha[4 * kb + 1], ha[4 * kb + 2], ha[4 * kb + 3], dW + kk * 128, kb > 0);
          }
          wgmma_commit();
        }
        if (jq == 0 && wg == 0) asm volatile("bar.arrive 2, 256;" ::: "memory");
        wgmma_wait<0>();
        if (jq == 0 && lane == 0) {
          __threadfence_block();
          if (atomicAdd(&relcnt[4], 1u) == 7u) {
            __threadfence_block();
            issue_items(smem, 36, 4);
          }
        }
        uint4* dstp = g_part + ((((size_t)rt * NJOB + jq) * 8 + warp) * 8 + sp) * 256 + lane;
#pragma unroll
        for (int i = 0; i < 8; i++)
          dstp[i * 32] = make_uint4(pack_bf16(acc[8 * i], acc[8 * i + 1]), pack_bf16(acc[8 * i + 2], acc[8 * i + 3]),
                                    pack_bf16(acc[8 * i + 4], acc[8 * i + 5]), pack_bf16(acc[8 * i + 6], acc[8 * i + 7]));
        __syncwarp();
        if (lane == 0) mbar_arrive(bar_st + 8 * jq);
        if (tid == 0) TS(5 + jq);
      }
}

__global__ void __launch_bounds__(NTHREADS, 1)
k_mega(const __nv_bfloat16* __restrict__ x, const __nv_bfloat16* __restrict__ wr, const __nv_bfloat16* __restrict__ wi,
       const __nv_bfloat16* __restrict__ w1, const __nv_bfloat16* __restrict__ b1, const __nv_bfloat16* __restrict__ b2,
       __nv_bfloat16* __restrict__ out, const __grid_constant__ Maps maps) {
  extern __shared__ __align__(1024) uint8_t smem[];
  const uint32_t sb = smem_u32(smem);
  const int rt = blockIdx.x >> 3, sp = blockIdx.x & 7;
  const int warp = threadIdx.x >> 5, lane = threadIdx.x & 31;
  const int s0 = blockIdx.x * 16;
  if (threadIdx.x == 0) TS(0);
  const uint32_t bar_full1 = sb + SM_BAR;
  const uint32_t bar_full2 = sb + SM_BAR + 64;
  unsigned* relcnt = reinterpret_cast<unsigned*>(smem + SM_BAR + 128);
  const uint32_t bar_stats = sb + SM_BAR + 160;
  const uint32_t bar_wt = sb + SM_BAR + 168;
  const uint32_t bar_tile = sb + SM_BAR + 176;
  const uint32_t bar_s = sb + SM_BAR + 184;
  const uint32_t bar_g = sb + SM_BAR + 192;
  const uint32_t bar_st = sb + SM_BAR + 224;
  uint8_t* tile = smem + SM_FFT;

  if (threadIdx.x == 0) {
    for (int i = 0; i < 4; i++) mbar_init(bar_full1 + 8 * i, 1);
    for (int i = 0; i < 8; i++) mbar_init(bar_full2 + 8 * i, 2);
    mbar_init(bar_stats, 1); mbar_init(bar_wt, 8); mbar_init(bar_tile, 1); mbar_init(bar_s, 128);
    for (int i = 0; i < 4; i++) { mbar_init(bar_g + 8 * i, 1); mbar_init(bar_st + 8 * i, 8); }
    for (int i = 0; i < 5; i++) relcnt[i] = 0;
    asm volatile("fence.mbarrier_init.release.cluster;" ::: "memory");
  }
  if (warp == 1) {
#pragma unroll 1
    for (int i = lane; i < 40; i += 32) {
      uint64_t mp; uint32_t dst, bar, bytes; int c0, c1, c2;
      if (i < 24) {
        const int j = (i * 11) >> 5, part = i - 3 * j;
        bar = bar_full1 + 8 * (j & 3);
        bytes = part ? 0 : STEP;
        dst = sb + (j & 3) * STEP + (part ? 16384 + (part - 1) * W1_STAGE : 0);
        mp = (uint64_t)(part ? &maps.w1 : &maps.x);
        c0 = part ? 0 : j * 64; c1 = part ? j * 64 + (part - 1) * 32 : rt * 128; c2 = part ? sp * 7 : 0;
      } else {
        const int p = i - 24;
        bar = bar_full2 + 8 * (p >> 1);
        bytes = W1_STAGE;
        dst = sb + piece_off(p);
        mp = (uint64_t)&maps.w2;
        c0 = (p >> 2) * 128 + (p & 1) * 64; c1 = sp * FC + ((p >> 1) & 1) * 112; c2 = 0;
      }
      *reinterpret_cast<uint4*>(smem + SM_TAB + i * 32) = make_uint4((uint32_t)mp, (uint32_t)(mp >> 32), dst, bar);
      *reinterpret_cast<uint4*>(smem + SM_TAB + i * 32 + 16) = make_uint4(c0, c1, c2, bytes);
    }
  }
  __syncthreads();
  if (threadIdx.x == 32 && blockIdx.x < 128) issue_items(smem, 0, 12);

  if (warp >= 8) {
    const int t = threadIdx.x & 127;
    const bool extra = blockIdx.x == 128;
    float2* buf = reinterpret_cast<float2*>(tile);
    const int k1 = t >> 3, m2 = t & 7;
    const int tq = (((t >> 3) & 1) << 2) | ((t >> 4) & 3) | ((t >> 6) << 3);
    const int c0 = extra ? 256 : blockIdx.x * 2;
    float2 vn[16];
    uint32_t wn[16], wq[16];
#pragma unroll 1
    for (int st = extra ? 4 : 0; st < 16; st++) {
      if (st == 0) {
        const uint2* xw = reinterpret_cast<const uint2*>(x + (size_t)(s0 + k1) * D_) + m2;
        uint2 w[16];
#pragma unroll
        for (int i = 0; i < 16; i++) w[i] = __ldg(xw + 8 * i);
        float sum = 0.f;
#pragma unroll
        for (int i = 0; i < 16; i++) sum += (bflo(w[i].x) + bfhi(w[i].x)) + (bflo(w[i].y) + bfhi(w[i].y));
#pragma unroll
        for (int o = 1; o < 8; o <<= 1) sum += __shfl_xor_sync(0xffffffffu, sum, o);
        const float mean = sum * (1.0f / D_);
        float sq = 0.f;
#pragma unroll
        for (int i = 0; i < 16; i++) {
          const float a = bflo(w[i].x) - mean, c = bfhi(w[i].x) - mean, d = bflo(w[i].y) - mean, e = bfhi(w[i].y) - mean;
          sq += (a * a + c * c) + (d * d + e * e);
        }
#pragma unroll
        for (int o = 1; o < 8; o <<= 1) sq += __shfl_xor_sync(0xffffffffu, sq, o);
        const uint32_t nm2 = pack_bf16(-mean, -mean);
        float sd, rs;
        asm("sqrt.approx.f32 %0, %1;" : "=f"(sd) : "f"(bf16r(bf16r(sq * (1.0f / D_)) + 1e-5f)));
        asm("rcp.approx.f32 %0, %1;" : "=f"(rs) : "f"(bf16r(sd)));
        if (m2 == 0) g_stats[s0 + k1] = make_float2(-bflo(nm2), rs);
#pragma unroll
        for (int i = 0; i < 32; i++) {
          const uint32_t d = hadd2_bf16((i & 1) ? w[i >> 1].y : w[i >> 1].x, nm2);
          const uint32_t xn = pack_bf16(bflo(d) * rs, bfhi(d) * rs);
          *tile_at(tile, 2 * (m2 + 8 * (i >> 1)) + (i & 1), k1) = make_float2(bflo(xn), bfhi(xn));
        }
        named_bar(3, 128);
        if (t == 0) TS(9);
      }
      if (st == 12) {
        named_bar(3, 128);
        if (t == 0) {
          TS(14);
          const unsigned target = grid_arrive(&g_bar[1]);
          if (!extra) {
            grid_wait(&g_bar[1], target);
            TS(15);
            fence_async();
            mbar_expect_tx(bar_tile, 32768);
            tma_load_2d(sb + SM_FFT, &maps.spec, s0, 0, bar_tile);
          }
        }
        if (extra) break;
        mbar_wait(bar_tile, 0);
      }
      if ((st == 4 && !extra) || st == 12) {
        const int r = t & 15;
        const float y256 = st == 12 ? __ldcg(&g_spec[(size_t)256 * S_ + s0 + r]).x : 0.f;
        const float sg = st == 4 ? -1.f : 1.f, sc = st == 4 ? 0.5f : 1.f;
#pragma unroll 2
        for (int j = t >> 4; j < 128; j += 8) {
          float2* pa = tile_at(tile, j, r);
          float2* pb = tile_at(tile, j == 0 ? 128 : 256 - j, r);
          const float2 A = *pa, B = *pb;
          const float2 P = make_float2(sc * (A.x + B.x), sc * (A.y - B.y)), M = make_float2(sc * (A.x - B.x), sc * (A.y + B.y));
          const float2 tw = twcs<512>(j);
          const float ts = sg * tw.y;
          const float2 T = make_float2(M.x * tw.x - M.y * ts, M.y * tw.x + M.x * ts);
          const float2 V = make_float2(-sg * T.y, sg * T.x);
          if (j) {
            *pa = make_float2(P.x + V.x, -sg * (P.y + V.y));
            *pb = make_float2(P.x - V.x, sg * (P.y - V.y));
          } else if (st == 4) {
            g_spec[(size_t)256 * S_ + s0 + r] = make_float2(A.x - A.y, 0.f);
            *pa = make_float2(A.x + A.y, 0.f);
            *pb = cconj(B);
          } else {
            *pa = make_float2(A.x + y256, y256 - A.x);
            *pb = make_float2(2.f * B.x, 2.f * B.y);
          }
        }
        fence_async();
        named_bar(3, 128);
      }
      if (st == 4) {
        if (t == 0) {
          TS(11);
          if (!extra) {
            tma_store_2d(&maps.spec, s0, 0, sb + SM_FFT);
            tma_store_commit_wait();
            mbar_wait(bar_wt, 0);
          }
          TS(12);
          const unsigned target = grid_arrive(&g_bar[0]);
          grid_wait(&g_bar[0], target);
          mbar_arrive(bar_stats);
        }
        named_bar(3, 128);
        if (t == 0) TS(13);
      }
      const bool colst = st >= 4 && st < 12;
      if (colst && (st & 3) == 0) {
#pragma unroll 1
        for (int c = (st == 4 ? 0 : 1); c < 2; c++) {
          if (c == 1) {
#pragma unroll
            for (int i = 0; i < 16; i++) { buf[128 * i + t] = vn[i]; wq[i] = wn[i]; }
          }
          if (st == 4) {
            const int cc = extra ? c0 : c0 + c;
#pragma unroll
            for (int i = 0; i < 16; i++) {
              vn[i] = __ldcg(g_spec + (size_t)cc * S_ + 128 * i + t);
              wn[i] = __ldcg(g_wt + (size_t)cc * S_ + 128 * i + t);
            }
          }
        }
      }
      {
        const int p = st & 1, r = (t & 7) + 8 * ((st >> 1) & 1);
        uint8_t* ta = reinterpret_cast<uint8_t*>(tile_at(tile, tq, r));
        const uint8_t* in = colst ? tile + (p ? k1 * 136 + m2 : t) * 8 : (p ? tile + tq * 2048 + (r & 1) * 8 : ta);
        const int is = colst ? (p ? 64 : 1024) : (p ? 128 : 2048);
        const int xs = (!colst && p) ? 16 : 0, xr = (r >> 1);
        float2 v[16];
#pragma unroll
        for (int i = 0; i < 16; i++) v[i] = *reinterpret_cast<const float2*>(in + i * is + ((xr ^ i) & 7) * xs);
        dft16<-1>(v);
        if (colst || !p) twiddle16(v, colst ? (p ? 16 * m2 : t) : 8 * tq);
        named_bar(3, 128);
        if (st >= 12 && p) {
          uint32_t* sw = reinterpret_cast<uint32_t*>(tile) + (t & 7) * SPITCH + tq;
#pragma unroll
          for (int i = 0; i < 16; i++) {
            const uint32_t sv = pack_bf16(v[O16(i)].x, -v[O16(i)].y);
            if (st == 13) wq[i] = sv;
            else { sw[16 * i] = wq[i]; sw[8 * SPITCH + 16 * i] = sv; }
          }
        } else {
          uint8_t* o = colst ? tile + (p ? k1 * 9 + m2 : t) * 8 : ta;
          const int os = colst ? (p ? 144 * 8 : 136 * 8) : 2048;
#pragma unroll
          for (int i = 0; i < 16; i++) *reinterpret_cast<float2*>(o + i * os) = v[O16(i)];
        }
        named_bar(3, 128);
      }
      if (colst && (st & 1)) {
        float2 e[2][8];
#pragma unroll
        for (int m = 0; m < 8; m++) { e[0][m] = buf[t * 9 + m]; e[1][m] = buf[(t + 128) * 9 + m]; }
        dft8<-1>(e[0]);
        dft8<-1>(e[1]);
        named_bar(3, 128);
        if (!(st & 2)) {
          constexpr float SC = 1.0f / (2048.0f * 512.0f);
#pragma unroll
          for (int i = 0; i < 16; i++)
            buf[128 * i + t] = cconj(cmul(e[i & 1][O8(i >> 1)], make_float2(bflo(wq[i]) * SC, bfhi(wq[i]) * SC)));
        } else {
          float2* col = g_spec + (size_t)(c0 + ((st - 4) >> 2)) * S_ + t;
#pragma unroll
          for (int i = 0; i < 16; i++) col[128 * i] = cconj(e[i & 1][O8(i >> 1)]);
          if (extra) st = 11;
        }
      }
    }
    if (extra) return;
    mbar_arrive(bar_s);
    if (t == 0) TS(16);
    if (warp == 9 && lane < 8) {
#pragma unroll 1
      for (int jq = 0; jq < NJOB; jq++) {
        mbar_wait(bar_st + 8 * jq, 0);
        __threadfence();
        atomicAdd(&g_flag[(rt * NJOB + jq) * 8 + lane], 1u);
      }
    }
    if (t == 64) {
      mbar_wait(bar_st + 24, 0);
#pragma unroll 1
      for (int jq = 0; jq < NJOB; jq++) {
        unsigned* fl = &g_flag[(rt * NJOB + jq) * 8 + sp];
        int it = 0;
        while (ld_acquire(fl) < 8u) {
          if (++it > (1 << 22)) __trap();
        }
        *fl = 0u;
        fence_async();
        mbar_expect_tx(bar_g + 8 * jq, jq ? 32768 : 32768 + 17 * 1024);
        if (jq == 0) {
#pragma unroll 1
          for (int i = 0; i < 17; i++)
            asm volatile("cp.async.bulk.shared::cluster.global.mbarrier::complete_tx::bytes [%0], [%1], %2, [%3];"
                         ::"r"(sb + 131072 + i * SPITCH * 4), "l"(i < 16 ? x + (size_t)(s0 + i) * D_ : b2), "r"(1024), "r"(bar_g) : "memory");
        }
        asm volatile("cp.async.bulk.shared::cluster.global.mbarrier::complete_tx::bytes [%0], [%1], %2, [%3];"
                     ::"r"(sb + jq * 32768), "l"(g_part + (((size_t)rt * NJOB + jq) * 8 + sp) * 8 * 256), "r"(32768), "r"(bar_g + 8 * jq) : "memory");
      }
    }
  } else {
    if (blockIdx.x == 128) return;
    const int tid = threadIdx.x;
    {
      const unsigned short* pr = reinterpret_cast<const unsigned short*>(wr) + (size_t)(s0 + (lane >> 4) * 8) * DF_ + warp * 32 + (lane & 15);
      const unsigned short* pi = reinterpret_cast<const unsigned short*>(wi) + (size_t)(s0 + (lane >> 4) * 8) * DF_ + warp * 32 + (lane & 15);
      uint32_t wv[16];
#pragma unroll
      for (int u = 0; u < 16; u++)
        wv[u] = (uint32_t)__ldg(pr + (u & 7) * DF_ + (u >> 3) * 16) | ((uint32_t)__ldg(pi + (u & 7) * DF_ + (u >> 3) * 16) << 16);
      if (tid < 16) {
        const size_t o = (size_t)(s0 + tid) * DF_ + 256;
        g_wt[(size_t)256 * S_ + s0 + tid] = (uint32_t)__ldg(reinterpret_cast<const unsigned short*>(wr) + o) |
                                            ((uint32_t)__ldg(reinterpret_cast<const unsigned short*>(wi) + o) << 16);
      }
      if ((tid & 127) < 112) {
        const uint32_t* pw = reinterpret_cast<const uint32_t*>(w1 + (size_t)(rt * 32 + (tid >> 7) * 16) * F_ + sp * FC) + (tid & 127);
        float c0 = 0.f, c1 = 0.f;
#pragma unroll
        for (int k = 0; k < 16; k++) { const uint32_t ww = __ldg(pw + k * (F_ / 2)); c0 += bflo(ww); c1 += bfhi(ww); }
        g_cs[(sp * 32 + rt * 2 + (tid >> 7)) * 112 + (tid & 127)] = make_float2(c0, c1);
      }
      const uint32_t stg = (uint32_t)(SM_WT + warp * 1024);
      const int kr = lane & 15;
#pragma unroll
      for (int rd = 0; rd < 2; rd++) {
        if (rd && lane == 0) asm volatile("cp.async.bulk.wait_group.read 0;" ::: "memory");
        __syncwarp();
#pragma unroll
        for (int c = 0; c < 2; c++)
          *reinterpret_cast<uint4*>(smem + stg + kr * 64 + ((((lane >> 4) * 2 + c) ^ ((kr >> 1) & 3)) << 4)) =
              make_uint4(wv[8 * rd + 4 * c], wv[8 * rd + 4 * c + 1], wv[8 * rd + 4 * c + 2], wv[8 * rd + 4 * c + 3]);
        fence_async();
        __syncwarp();
        if (lane == 0) {
          tma_store_2d(&maps.wt, s0, warp * 32 + rd * 16, sb + stg);
          asm volatile("cp.async.bulk.commit_group;" ::: "memory");
        }
      }
    }
    gemm_part(smem, maps, b1, rt, sp);
    {
      const int g = lane >> 2;
      const uint32_t* stile = reinterpret_cast<const uint32_t*>(tile);
      const uint32_t* xs = reinterpret_cast<const uint32_t*>(smem + 131072);
      mbar_wait(bar_s, 0);
      if (tid == 0) TS(17);
#pragma unroll 1
      for (int jq = 0; jq < NJOB; jq++) {
        const int cw = jq * 64 + 8 * warp + (lane & 3);
        mbar_wait(bar_g + 8 * jq, 0);
        const uint4* src = reinterpret_cast<const uint4*>(smem + jq * 32768) + tid;
        float o[8];
#pragma unroll
        for (int c = 0; c < 8; c++) o[c] = 0.f;
#pragma unroll
        for (int s = 0; s < 8; s++) {
          const uint4 v = src[s * 256];
          o[0] += bflo(v.x); o[1] += bfhi(v.x); o[2] += bflo(v.y); o[3] += bfhi(v.y);
          o[4] += bflo(v.z); o[5] += bfhi(v.z); o[6] += bflo(v.w); o[7] += bfhi(v.w);
        }
#pragma unroll
        for (int c = 0; c < 4; c++) {
          const int row = g + 8 * (c & 1), w = cw + 4 * (c >> 1);
          const uint32_t sw = stile[row * SPITCH + w];
          const uint32_t p = hadd2_bf16(pack_bf16(0.5f * o[2 * c], 0.5f * o[2 * c + 1]), xs[16 * SPITCH + w]);
          const float oa = bflo(p), ob = bfhi(p);
          const uint32_t gg = pack_bf16(__fdividef(oa, 1.0f + __expf(-oa)), __fdividef(ob, 1.0f + __expf(-ob)));
          const uint32_t sg = pack_bf16(bflo(sw) * bflo(gg), bfhi(sw) * bfhi(gg));
          reinterpret_cast<uint32_t*>(out)[(size_t)(s0 + row) * 256 + w] = hadd2_bf16(xs[row * SPITCH + w], sg);
        }
        if (tid == 0) TS(20 + jq);
      }
    }
  }
}

typedef CUresult (*EncodeFn)(CUtensorMap*, CUtensorMapDataType, cuuint32_t, void*, const cuuint64_t*, const cuuint64_t*,
                             const cuuint32_t*, const cuuint32_t*, CUtensorMapInterleave, CUtensorMapSwizzle,
                             CUtensorMapL2promotion, CUtensorMapFloatOOBfill);

}

extern "C" void kernel_launch(void* const* d_in, const int* in_sizes, int n_in, void* d_out, int out_size) {
  const __nv_bfloat16* x = (const __nv_bfloat16*)d_in[0];
  const __nv_bfloat16* wr = (const __nv_bfloat16*)d_in[1];
  const __nv_bfloat16* wi = (const __nv_bfloat16*)d_in[2];
  const __nv_bfloat16* w1 = (const __nv_bfloat16*)d_in[4];
  const __nv_bfloat16* b1 = (const __nv_bfloat16*)d_in[5];
  const __nv_bfloat16* w2 = (const __nv_bfloat16*)d_in[6];
  const __nv_bfloat16* b2 = (const __nv_bfloat16*)d_in[7];
  __nv_bfloat16* out = (__nv_bfloat16*)d_out;

  static EncodeFn enc = nullptr;
  static void* p_spec = nullptr;
  static void* p_wt = nullptr;
  if (!enc) {
    void* fn = nullptr;
    cudaDriverEntryPointQueryResult qr;
    cudaGetDriverEntryPoint("cuTensorMapEncodeTiled", &fn, cudaEnableDefault, &qr);
    enc = (EncodeFn)fn;
    cudaFuncSetAttribute(k_mega, cudaFuncAttributeMaxDynamicSharedMemorySize, SM_TOTAL);
    cudaGetSymbolAddress(&p_spec, g_spec);
    cudaGetSymbolAddress(&p_wt, g_wt);
  }
  Maps m;
  const cuuint32_t es[3] = {1, 1, 1};
  {
    cuuint64_t dims[3] = {(cuuint64_t)D_, (cuuint64_t)S_, 1};
    cuuint64_t strides[2] = {(cuuint64_t)D_ * 2, (cuuint64_t)D_ * 2 * S_};
    cuuint32_t box[3] = {64, 128, 1};
    enc(&m.x, CU_TENSOR_MAP_DATA_TYPE_BFLOAT16, 3, (void*)x, dims, strides, box, es, CU_TENSOR_MAP_INTERLEAVE_NONE,
        CU_TENSOR_MAP_SWIZZLE_128B, CU_TENSOR_MAP_L2_PROMOTION_L2_128B, CU_TENSOR_MAP_FLOAT_OOB_FILL_NONE);
  }
  {
    cuuint64_t dims[3] = {32, 512, 56};
    cuuint64_t strides[2] = {(cuuint64_t)F_ * 2, 64};
    cuuint32_t box[3] = {32, 32, 7};
    enc(&m.w1, CU_TENSOR_MAP_DATA_TYPE_BFLOAT16, 3, (void*)w1, dims, strides, box, es, CU_TENSOR_MAP_INTERLEAVE_NONE,
        CU_TENSOR_MAP_SWIZZLE_64B, CU_TENSOR_MAP_L2_PROMOTION_L2_128B, CU_TENSOR_MAP_FLOAT_OOB_FILL_NONE);
  }
  {
    cuuint64_t dims[3] = {(cuuint64_t)D_, (cuuint64_t)F_, 1};
    cuuint64_t strides[2] = {(cuuint64_t)D_ * 2, (cuuint64_t)D_ * 2 * F_};
    cuuint32_t box[3] = {64, 112, 1};
    enc(&m.w2, CU_TENSOR_MAP_DATA_TYPE_BFLOAT16, 3, (void*)w2, dims, strides, box, es, CU_TENSOR_MAP_INTERLEAVE_NONE,
        CU_TENSOR_MAP_SWIZZLE_128B, CU_TENSOR_MAP_L2_PROMOTION_L2_128B, CU_TENSOR_MAP_FLOAT_OOB_FILL_NONE);
  }
  {
    cuuint64_t dims[2] = {(cuuint64_t)S_, 256};
    cuuint64_t strides[1] = {(cuuint64_t)S_ * 8};
    cuuint32_t box[2] = {16, 256};
    enc(&m.spec, CU_TENSOR_MAP_DATA_TYPE_FLOAT64, 2, p_spec, dims, strides, box, es, CU_TENSOR_MAP_INTERLEAVE_NONE,
        CU_TENSOR_MAP_SWIZZLE_128B, CU_TENSOR_MAP_L2_PROMOTION_NONE, CU_TENSOR_MAP_FLOAT_OOB_FILL_NONE);
  }
  {
    cuuint64_t dims[2] = {(cuuint64_t)S_, 257};
    cuuint64_t strides[1] = {(cuuint64_t)S_ * 4};
    cuuint32_t box[2] = {16, 16};
    enc(&m.wt, CU_TENSOR_MAP_DATA_TYPE_UINT32, 2, p_wt, dims, strides, box, es, CU_TENSOR_MAP_INTERLEAVE_NONE,
        CU_TENSOR_MAP_SWIZZLE_64B, CU_TENSOR_MAP_L2_PROMOTION_NONE, CU_TENSOR_MAP_FLOAT_OOB_FILL_NONE);
  }
  k_mega<<<129, NTHREADS, SM_TOTAL>>>(x, wr, wi, w1, b1, b2, out, m);
}
```

```cpp
#include <cuda_runtime.h>
#include <cuda_bf16.h>
#include <cuda.h>
#include <stdint.h>

namespace {

constexpr int S_ = 2048, D_ = 512, F_ = 1792, DF_ = 257;
constexpr int FC = 224;
constexpr int NJOB = 4;

__device__ __align__(1024) float2 g_spec[257 * 2048];
__device__ __align__(1024) uint32_t g_wt[257 * 2048];
__device__ uint4 g_part[16 * NJOB * 8 * 8 * 256];
__device__ float2 g_cs[8 * 32 * 112];
__device__ float2 g_stats[2048];
__device__ unsigned g_bar[2];
__device__ unsigned g_flag[16 * NJOB * 8];
#define TS(i)

__device__ __forceinline__ uint32_t smem_u32(const void* p) { return (uint32_t)__cvta_generic_to_shared(p); }
__device__ __forceinline__ float bf16r(float x) { return __bfloat162float(__float2bfloat16_rn(x)); }
__device__ __forceinline__ float bflo(uint32_t w) { return __uint_as_float(w << 16); }
__device__ __forceinline__ float bfhi(uint32_t w) { return __uint_as_float(w & 0xffff0000u); }
__device__ __forceinline__ uint32_t pack_bf16(float lo, float hi) {
  uint32_t r;
  asm("cvt.rn.bf16x2.f32 %0, %1, %2;" : "=r"(r) : "f"(hi), "f"(lo));
  return r;
}
__device__ __forceinline__ uint32_t hadd2_bf16(uint32_t a, uint32_t b) {
  uint32_t r;
  asm("add.rn.bf16x2 %0, %1, %2;" : "=r"(r) : "r"(a), "r"(b));
  return r;
}
__device__ __forceinline__ void named_bar(int id, int n) { asm volatile("bar.sync %0, %1;" ::"r"(id), "r"(n) : "memory"); }
__device__ __forceinline__ void fence_async() { asm volatile("fence.proxy.async;" ::: "memory"); }

__device__ __forceinline__ void mbar_init(uint32_t bar, int cnt) { asm volatile("mbarrier.init.shared::cta.b64 [%0], %1;" ::"r"(bar), "r"(cnt) : "memory"); }
__device__ __forceinline__ void mbar_expect_tx(uint32_t bar, uint32_t bytes) { asm volatile("mbarrier.arrive.expect_tx.shared::cta.b64 _, [%0], %1;" ::"r"(bar), "r"(bytes) : "memory"); }
__device__ __forceinline__ void mbar_arrive(uint32_t bar) { asm volatile("mbarrier.arrive.shared::cta.b64 _, [%0];" ::"r"(bar) : "memory"); }
__device__ __forceinline__ bool mbar_try(uint32_t bar, uint32_t parity) {
  uint32_t ok;
  asm volatile("{\n.reg .pred p;\nmbarrier.try_wait.parity.shared::cta.b64 p, [%1], %2, %3;\nselp.u32 %0, 1, 0, p;\n}\n" : "=r"(ok) : "r"(bar), "r"(parity), "r"(20000u) : "memory");
  return ok != 0;
}
__device__ __forceinline__ void mbar_wait(uint32_t bar, uint32_t parity) {
  int it = 0;
  while (!mbar_try(bar, parity)) {
    if (++it > (1 << 22)) __trap();
  }
}
__device__ __forceinline__ void tma_load_3d(uint32_t dst, const CUtensorMap* map, int c0, int c1, int c2, uint32_t bar) {
  asm volatile("cp.async.bulk.tensor.3d.shared::cluster.global.mbarrier::complete_tx::bytes [%0], [%1, {%3, %4, %5}], [%2];"
               ::"r"(dst), "l"((uint64_t)map), "r"(bar), "r"(c0), "r"(c1), "r"(c2) : "memory");
}
__device__ __forceinline__ void tma_load_2d(uint32_t dst, const CUtensorMap* map, int c0, int c1, uint32_t bar) {
  asm volatile("cp.async.bulk.tensor.2d.shared::cluster.global.mbarrier::complete_tx::bytes [%0], [%1, {%3, %4}], [%2];"
               ::"r"(dst), "l"((uint64_t)map), "r"(bar), "r"(c0), "r"(c1) : "memory");
}
__device__ __forceinline__ void tma_store_2d(const CUtensorMap* map, int c0, int c1, uint32_t src) {
  asm volatile("cp.async.bulk.tensor.2d.global.shared::cta.bulk_group [%0, {%2, %3}], [%1];"
               ::"l"((uint64_t)map), "r"(src), "r"(c0), "r"(c1) : "memory");
}
__device__ __forceinline__ void tma_store_commit_wait() {
  asm volatile("cp.async.bulk.commit_group;" ::: "memory");
  asm volatile("cp.async.bulk.wait_group 0;" ::: "memory");
}
__device__ __forceinline__ void wgmma_fence() { asm volatile("wgmma.fence.sync.aligned;" ::: "memory"); }
__device__ __forceinline__ void wgmma_commit() { asm volatile("wgmma.commit_group.sync.aligned;" ::: "memory"); }
template <int N> __device__ __forceinline__ void wgmma_wait() { asm volatile("wgmma.wait_group.sync.aligned %0;" ::"n"(N) : "memory"); }
__device__ __forceinline__ uint64_t make_desc(uint32_t addr, uint32_t lbo_bytes, uint32_t sbo_bytes, uint32_t swz) {
  uint64_t d = 0;
  d |= (uint64_t)((addr & 0x3FFFF) >> 4);
  d |= (uint64_t)((lbo_bytes & 0x3FFFF) >> 4) << 16;
  d |= (uint64_t)((sbo_bytes & 0x3FFFF) >> 4) << 32;
  d |= (uint64_t)swz << 62;
  return d;
}
__device__ __forceinline__ unsigned ld_acquire(const unsigned* p) {
  unsigned v;
  asm volatile("ld.acquire.gpu.global.u32 %0, [%1];" : "=r"(v) : "l"(p) : "memory");
  return v;
}

__device__ __forceinline__ void wgmma_n224_ss(float (&d)[112], uint64_t da, uint64_t db, int scale_d) {
  asm volatile("{\n.reg .pred p;\nsetp.ne.b32 p, %114, 0;\n"
    "wgmma.mma_async.sync.aligned.m64n224k16.f32.bf16.bf16 {%0, %1, %2, %3, %4, %5, %6, %7, %8, %9, %10, %11, %12, %13, %14, %15, %16, %17, %18, %19, %20, %21, %22, %23, %24, %25, %26, %27, %28, %29, %30, %31, %32, %33, %34, %35, %36, %37, %38, %39, %40, %41, %42, %43, %44, %45, %46, %47, %48, %49, %50, %51, %52, %53, %54, %55, %56, %57, %58, %59, %60, %61, %62, %63, %64, %65, %66, %67, %68, %69, %70, %71, %72, %73, %74, %75, %76, %77, %78, %79, %80, %81, %82, %83, %84, %85, %86, %87, %88, %89, %90, %91, %92, %93, %94, %95, %96, %97, %98, %99, %100, %101, %102, %103, %104, %105, %106, %107, %108, %109, %110, %111}, %112, %113, p, 1, 1, 0, 1;\n}\n"
    : "+f"(d[0]), "+f"(d[1]), "+f"(d[2]), "+f"(d[3]), "+f"(d[4]), "+f"(d[5]), "+f"(d[6]), "+f"(d[7]), "+f"(d[8]), "+f"(d[9]), "+f"(d[10]), "+f"(d[11]), "+f"(d[12]), "+f"(d[13]), "+f"(d[14]), "+f"(d[15]), "+f"(d[16]), "+f"(d[17]), "+f"(d[18]), "+f"(d[19]), "+f"(d[20]), "+f"(d[21]), "+f"(d[22]), "+f"(d[23]), "+f"(d[24]), "+f"(d[25]), "+f"(d[26]), "+f"(d[27]), "+f"(d[28]), "+f"(d[29]), "+f"(d[30]), "+f"(d[31]), "+f"(d[32]), "+f"(d[33]), "+f"(d[34]), "+f"(d[35]), "+f"(d[36]), "+f"(d[37]), "+f"(d[38]), "+f"(d[39]), "+f"(d[40]), "+f"(d[41]), "+f"(d[42]), "+f"(d[43]), "+f"(d[44]), "+f"(d[45]), "+f"(d[46]), "+f"(d[47]), "+f"(d[48]), "+f"(d[49]), "+f"(d[50]), "+f"(d[51]), "+f"(d[52]), "+f"(d[53]), "+f"(d[54]), "+f"(d[55]), "+f"(d[56]), "+f"(d[57]), "+f"(d[58]), "+f"(d[59]), "+f"(d[60]), "+f"(d[61]), "+f"(d[62]), "+f"(d[63]), "+f"(d[64]), "+f"(d[65]), "+f"(d[66]), "+f"(d[67]), "+f"(d[68]), "+f"(d[69]), "+f"(d[70]), "+f"(d[71]), "+f"(d[72]), "+f"(d[73]), "+f"(d[74]), "+f"(d[75]), "+f"(d[76]), "+f"(d[77]), "+f"(d[78]), "+f"(d[79]), "+f"(d[80]), "+f"(d[81]), "+f"(d[82]), "+f"(d[83]), "+f"(d[84]), "+f"(d[85]), "+f"(d[86]), "+f"(d[87]), "+f"(d[88]), "+f"(d[89]), "+f"(d[90]), "+f"(d[91]), "+f"(d[92]), "+f"(d[93]), "+f"(d[94]), "+f"(d[95]), "+f"(d[96]), "+f"(d[97]), "+f"(d[98]), "+f"(d[99]), "+f"(d[100]), "+f"(d[101]), "+f"(d[102]), "+f"(d[103]), "+f"(d[104]), "+f"(d[105]), "+f"(d[106]), "+f"(d[107]), "+f"(d[108]), "+f"(d[109]), "+f"(d[110]), "+f"(d[111])
    : "l"(da), "l"(db), "r"(scale_d));
}
__device__ __forceinline__ void wgmma_n128_rs(float (&d)[64], uint32_t a0, uint32_t a1, uint32_t a2, uint32_t a3, uint64_t db, int scale_d) {
  asm volatile("{\n.reg .pred p;\nsetp.ne.b32 p, %69, 0;\n"
    "wgmma.mma_async.sync.aligned.m64n128k16.f32.bf16.bf16 {%0, %1, %2, %3, %4, %5, %6, %7, %8, %9, %10, %11, %12, %13, %14, %15, %16, %17, %18, %19, %20, %21, %22, %23, %24, %25, %26, %27, %28, %29, %30, %31, %32, %33, %34, %35, %36, %37, %38, %39, %40, %41, %42, %43, %44, %45, %46, %47, %48, %49, %50, %51, %52, %53, %54, %55, %56, %57, %58, %59, %60, %61, %62, %63}, {%64, %65, %66, %67}, %68, p, 1, 1, 1;\n}\n"
    : "+f"(d[0]), "+f"(d[1]), "+f"(d[2]), "+f"(d[3]), "+f"(d[4]), "+f"(d[5]), "+f"(d[6]), "+f"(d[7]), "+f"(d[8]), "+f"(d[9]), "+f"(d[10]), "+f"(d[11]), "+f"(d[12]), "+f"(d[13]), "+f"(d[14]), "+f"(d[15]), "+f"(d[16]), "+f"(d[17]), "+f"(d[18]), "+f"(d[19]), "+f"(d[20]), "+f"(d[21]), "+f"(d[22]), "+f"(d[23]), "+f"(d[24]), "+f"(d[25]), "+f"(d[26]), "+f"(d[27]), "+f"(d[28]), "+f"(d[29]), "+f"(d[30]), "+f"(d[31]), "+f"(d[32]), "+f"(d[33]), "+f"(d[34]), "+f"(d[35]), "+f"(d[36]), "+f"(d[37]), "+f"(d[38]), "+f"(d[39]), "+f"(d[40]), "+f"(d[41]), "+f"(d[42]), "+f"(d[43]), "+f"(d[44]), "+f"(d[45]), "+f"(d[46]), "+f"(d[47]), "+f"(d[48]), "+f"(d[49]), "+f"(d[50]), "+f"(d[51]), "+f"(d[52]), "+f"(d[53]), "+f"(d[54]), "+f"(d[55]), "+f"(d[56]), "+f"(d[57]), "+f"(d[58]), "+f"(d[59]), "+f"(d[60]), "+f"(d[61]), "+f"(d[62]), "+f"(d[63])
    : "r"(a0), "r"(a1), "r"(a2), "r"(a3), "l"(db), "r"(scale_d));
}

__device__ __forceinline__ float2 cadd(float2 a, float2 b) { return make_float2(a.x + b.x, a.y + b.y); }
__device__ __forceinline__ float2 csub(float2 a, float2 b) { return make_float2(a.x - b.x, a.y - b.y); }
__device__ __forceinline__ float2 cmul(float2 a, float2 b) { return make_float2(a.x * b.x - a.y * b.y, a.x * b.y + a.y * b.x); }
__device__ __forceinline__ float2 cconj(float2 a) { return make_float2(a.x, -a.y); }

template <int DIR> __device__ __forceinline__ void dft4(float2& a0, float2& a1, float2& a2, float2& a3) {
  float2 t0 = cadd(a0, a2), t1 = csub(a0, a2), t2 = cadd(a1, a3), t3 = csub(a1, a3);
  float2 t3r = DIR < 0 ? make_float2(t3.y, -t3.x) : make_float2(-t3.y, t3.x);
  a0 = cadd(t0, t2); a2 = csub(t0, t2); a1 = cadd(t1, t3r); a3 = csub(t1, t3r);
}
template <int DIR> __device__ __forceinline__ float2 mulw(float2 v, float c, float s) {
  return DIR < 0 ? make_float2(v.x * c + v.y * s, v.y * c - v.x * s) : make_float2(v.x * c - v.y * s, v.y * c + v.x * s);
}
template <int DIR> __device__ __forceinline__ float2 muli(float2 v) {
  return DIR < 0 ? make_float2(v.y, -v.x) : make_float2(-v.y, v.x);
}
#define O16(k) (4 * ((k) & 3) + ((k) >> 2))
#define O8(k) (2 * ((k) & 3) + ((k) >> 2))
template <int DIR> __device__ __forceinline__ void dft16(float2 (&v)[16]) {
  constexpr float C1 = 0.92387953251128674f, S1 = 0.38268343236508977f, R = 0.70710678118654752f;
#pragma unroll
  for (int n2 = 0; n2 < 4; n2++) dft4<DIR>(v[n2], v[4 + n2], v[8 + n2], v[12 + n2]);
  v[5] = mulw<DIR>(v[5], C1, S1);
  v[6] = mulw<DIR>(v[6], R, R);
  v[7] = mulw<DIR>(v[7], S1, C1);
  v[9] = mulw<DIR>(v[9], R, R);
  v[10] = muli<DIR>(v[10]);
  v[11] = mulw<DIR>(v[11], -R, R);
  v[13] = mulw<DIR>(v[13], S1, C1);
  v[14] = mulw<DIR>(v[14], -R, R);
  v[15] = mulw<DIR>(v[15], -C1, -S1);
#pragma unroll
  for (int k1 = 0; k1 < 4; k1++) dft4<DIR>(v[4 * k1], v[4 * k1 + 1], v[4 * k1 + 2], v[4 * k1 + 3]);
}
template <int DIR> __device__ __forceinline__ void dft8(float2 (&v)[8]) {
  constexpr float R = 0.70710678118654752f;
  dft4<DIR>(v[0], v[2], v[4], v[6]);
  dft4<DIR>(v[1], v[3], v[5], v[7]);
  v[3] = mulw<DIR>(v[3], R, R);
  v[5] = muli<DIR>(v[5]);
  v[7] = mulw<DIR>(v[7], -R, R);
#pragma unroll
  for (int k1 = 0; k1 < 4; k1++) {
    float2 a = v[2 * k1], b = v[2 * k1 + 1];
    v[2 * k1] = cadd(a, b); v[2 * k1 + 1] = csub(a, b);
  }
}
template <int N> __device__ __forceinline__ float2 twcs(int m) {
  m &= (N - 1);
  if (m >= N / 2) m -= N;
  float s, c;
  __sincosf((float)m * (6.283185307179586f / N), &s, &c);
  return make_float2(c, s);
}

__device__ __forceinline__ void twiddle16(float2 (&v)[16], int m) {
  const float2 w1 = twcs<2048>(m), w2 = twcs<2048>(2 * m);
  float2 wo = w1, we = w2;
#pragma unroll
  for (int k = 1; k < 16; k += 2) {
    v[O16(k)] = mulw<-1>(v[O16(k)], wo.x, wo.y);
    if (k < 15) {
      v[O16(k + 1)] = mulw<-1>(v[O16(k + 1)], we.x, we.y);
      wo = cmul(wo, w2);
      if (k < 13) we = cmul(we, w2);
    }
  }
}
__device__ __forceinline__ float2* tile_at(uint8_t* tile, int k, int r) {
  return reinterpret_cast<float2*>(tile + k * 128 + ((((r >> 1) ^ k) & 7) << 4) + (r & 1) * 8);
}
constexpr int SPITCH = 260;

constexpr int STEP = 45056;
constexpr int W1_STAGE = 14336;
constexpr int SM_FFT = 184 * 1024;
constexpr int SM_WT = SM_FFT + 32768;
constexpr int SM_BAR = SM_WT + 8192;
constexpr int SM_TAB = SM_BAR + 256;
constexpr int SM_TOTAL = SM_TAB + 1280;
constexpr int NTHREADS = 384;

__device__ __forceinline__ float gelu2(float x) {
  float u = x * (0.7978845608028654f + 0.035677408136300125f * x * x);
  float th;
  asm("tanh.approx.f32 %0, %1;" : "=f"(th) : "f"(u));
  return fmaf(x, th, x);
}
__device__ __forceinline__ unsigned grid_arrive(unsigned* cnt) {
  __threadfence();
  unsigned old = atomicAdd(cnt, 1u);
  return (old / 129u + 1u) * 129u;
}
__device__ __forceinline__ void grid_wait(const unsigned* cnt, unsigned target) {
  int it = 0;
  while ((int)(ld_acquire(cnt) - target) < 0) {
    if (++it > (1 << 22)) __trap();
  }
}
__device__ __forceinline__ uint32_t piece_off(int p) {
  if (p >= 12) p -= 12;
  const int s = (p * 11) >> 5;
  return (uint32_t)(s * STEP + (p - 3 * s) * W1_STAGE);
}

struct Maps { CUtensorMap x, w1, w2, spec, wt; };

__device__ __forceinline__ void issue_items(const uint8_t* smem, int first, int n) {
#pragma unroll 1
  for (int i = first; i < first + n; i++) {
    const uint4 a = *reinterpret_cast<const uint4*>(smem + SM_TAB + i * 32);
    const uint4 c = *reinterpret_cast<const uint4*>(smem + SM_TAB + i * 32 + 16);
    if (c.w) mbar_expect_tx(a.w, c.w);
    tma_load_3d(a.z, reinterpret_cast<const CUtensorMap*>((uint64_t)a.x | ((uint64_t)a.y << 32)), (int)c.x, (int)c.y, (int)c.z, a.w);
  }
}

__device__ __forceinline__ void gemm_part(uint8_t* smem, const Maps& maps, const __nv_bfloat16* __restrict__ b1, int rt, int sp) {
  const uint32_t sb = smem_u32(smem);
  const int tid = threadIdx.x, warp = tid >> 5, lane = tid & 31, wg = warp >> 2;
  const uint32_t bar_full1 = sb + SM_BAR, bar_full2 = sb + SM_BAR + 64;
  unsigned* relcnt = reinterpret_cast<unsigned*>(smem + SM_BAR + 128);
  const uint32_t bar_stats = sb + SM_BAR + 160, bar_st = sb + SM_BAR + 224;
  uint32_t ha[56];
      auto release = [&](int j) {
        __syncwarp();
        if (lane == 0) {
          __threadfence_block();
          if ((atomicAdd(&relcnt[j & 3], 1u) & 7u) == 7u) {
            __threadfence_block();
            issue_items(smem, 3 * j + 12, 3);
          }
        }
      };
      {
        float acc[112];
#pragma unroll
        for (int i = 0; i < 112; i++) acc[i] = 0.f;
        const uint64_t dA = make_desc(sb + __shfl_sync(0xffffffffu, wg, 0) * 8192, 16, 1024, 1), dB = make_desc(sb + 16384, 2048, 512, 2);
#pragma unroll 1
        for (int j = 0; j < 8; j++) {
          const uint32_t base = (j & 3) * STEP;
          mbar_wait(bar_full1 + 8 * (j & 3), j >> 2);
          if (tid == 0) TS(24 + j);
          wgmma_fence();
#pragma unroll
          for (int kk = 0; kk < 4; kk++)
            wgmma_n224_ss(acc, dA + ((base + kk * 32) >> 4), dB + ((base + (kk >> 1) * W1_STAGE + (kk & 1) * 1024) >> 4), 1);
          wgmma_commit();
          if (j > 0) {
            wgmma_wait<1>();
            release(j - 1);
          }
        }
        mbar_wait(bar_stats, 0);
        if (tid < 224) {
          float c0 = 0.f, c1 = 0.f;
          const float2* pc = g_cs + (sp * 32 + (tid & 1) * 16) * 112 + (tid >> 1);
#pragma unroll
          for (int i = 0; i < 16; i++) { const float2 c = __ldcg(pc + i * 112); c0 += c.x; c1 += c.y; }
          c0 += __shfl_xor_sync(0xffffffffu, c0, 1); c1 += __shfl_xor_sync(0xffffffffu, c1, 1);
          const uint32_t bw = __ldg(reinterpret_cast<const uint32_t*>(b1 + sp * FC) + (tid >> 1));
          reinterpret_cast<float4*>(smem + SM_WT)[tid >> 1] = make_float4(c0, c1, bflo(bw), bfhi(bw));
        }
        const int row = rt * 128 + warp * 16 + (lane >> 2);
        const float2 st0 = __ldcg(&g_stats[row]), st1 = __ldcg(&g_stats[row + 8]);
        wgmma_wait<0>();
        if (tid == 0) TS(2);
        named_bar(1, 256);
        if (tid == 0) {
          issue_items(smem, 33, 3);
        }
        if (tid == 0) TS(3);
        const float4* csb = reinterpret_cast<const float4*>(smem + SM_WT) + (lane & 3);
#pragma unroll
        for (int j = 0; j < 28; j++) {
          const float4 c = csb[j * 4];
          ha[2 * j] = pack_bf16(gelu2(fmaf(fmaf(-st0.x, c.x, acc[4 * j]), st0.y, c.z)), gelu2(fmaf(fmaf(-st0.x, c.y, acc[4 * j + 1]), st0.y, c.w)));
          ha[2 * j + 1] = pack_bf16(gelu2(fmaf(fmaf(-st1.x, c.x, acc[4 * j + 2]), st1.y, c.z)), gelu2(fmaf(fmaf(-st1.x, c.y, acc[4 * j + 3]), st1.y, c.w)));
        }
      }
      if (tid == 0) TS(4);
      if (wg == 1) named_bar(2, 256);
#pragma unroll 1
      for (int jq = 0; jq < NJOB; jq++) {
        float acc[64];
#pragma unroll
        for (int h = 0; h < 2; h++) {
          const uint32_t o0 = piece_off(4 * jq + 2 * h), o1 = piece_off(4 * jq + 2 * h + 1);
          const uint64_t dW = make_desc(sb + o0, o1 - o0, 1024, 1);
          mbar_wait(bar_full2 + 8 * (2 * jq + h), 0);
          wgmma_fence();
#pragma unroll
          for (int kk = 0; kk < 7; kk++) {
            const int kb = h * 7 + kk;
            wgmma_n128_rs(acc, ha[4 * kb], ha[4 * kb + 1], ha[4 * kb + 2], ha[4 * kb + 3], dW + kk * 128, kb > 0);
          }
          wgmma_commit();
        }
        if (jq == 0 && wg == 0) asm volatile("bar.arrive 2, 256;" ::: "memory");
        wgmma_wait<0>();
        if (jq == 0 && lane == 0) {
          __threadfence_block();
          if (atomicAdd(&relcnt[4], 1u) == 7u) {
            __threadfence_block();
            issue_items(smem, 36, 4);
          }
        }
        uint4* dstp = g_part + ((((size_t)rt * NJOB + jq) * 8 + warp) * 8 + sp) * 256 + lane;
#pragma unroll
        for (int i = 0; i < 8; i++)
          dstp[i * 32] = make_uint4(pack_bf16(acc[8 * i], acc[8 * i + 1]), pack_bf16(acc[8 * i + 2], acc[8 * i + 3]),
                                    pack_bf16(acc[8 * i + 4], acc[8 * i + 5]), pack_bf16(acc[8 * i + 6], acc[8 * i + 7]));
        __syncwarp();
        if (lane == 0) mbar_arrive(bar_st + 8 * jq);
        if (tid == 0) TS(5 + jq);
      }
}

__global__ void __launch_bounds__(NTHREADS, 1)
k_mega(const __nv_bfloat16* __restrict__ x, const __nv_bfloat16* __restrict__ wr, const __nv_bfloat16* __restrict__ wi,
       const __nv_bfloat16* __restrict__ w1, const __nv_bfloat16* __restrict__ b1, const __nv_bfloat16* __restrict__ b2, __nv_bfloat16* __restrict__ out,
       const __grid_constant__ Maps maps) {
  extern __shared__ __align__(1024) uint8_t smem[];
  const uint32_t sb = smem_u32(smem);
  const int rt = blockIdx.x >> 3, sp = blockIdx.x & 7;
  const int warp = threadIdx.x >> 5, lane = threadIdx.x & 31;
  const int s0 = blockIdx.x * 16;
  if (threadIdx.x == 0) TS(0);
  const uint32_t bar_full1 = sb + SM_BAR;
  const uint32_t bar_full2 = sb + SM_BAR + 64;
  unsigned* relcnt = reinterpret_cast<unsigned*>(smem + SM_BAR + 128);
  const uint32_t bar_stats = sb + SM_BAR + 160;
  const uint32_t bar_p1 = sb + SM_BAR + 168;
  const uint32_t bar_tile = sb + SM_BAR + 176;
  const uint32_t bar_st = sb + SM_BAR + 224;
  const uint32_t bar_g = sb + SM_BAR + 192;
  uint8_t* tile = smem + SM_FFT;

  if (threadIdx.x == 0) {
    for (int i = 0; i < 4; i++) mbar_init(bar_full1 + 8 * i, 1);
    for (int i = 0; i < 8; i++) mbar_init(bar_full2 + 8 * i, 2);
    mbar_init(bar_stats, 1); mbar_init(bar_p1, 256); mbar_init(bar_tile, 1);
    for (int i = 0; i < 4; i++) { mbar_init(bar_g + 8 * i, 1); mbar_init(bar_st + 8 * i, 8); }
    for (int i = 0; i < 5; i++) relcnt[i] = 0;
    asm volatile("fence.mbarrier_init.release.cluster;" ::: "memory");
  }
  if (warp == 1) {
#pragma unroll 1
    for (int i = lane; i < 40; i += 32) {
      uint64_t mp; uint32_t dst, bar, bytes; int c0, c1, c2;
      if (i < 24) {
        const int j = (i * 11) >> 5, part = i - 3 * j;
        bar = bar_full1 + 8 * (j & 3);
        bytes = part ? 0 : STEP;
        dst = sb + (j & 3) * STEP + (part ? 16384 + (part - 1) * W1_STAGE : 0);
        mp = (uint64_t)(part ? &maps.w1 : &maps.x);
        c0 = part ? 0 : j * 64; c1 = part ? j * 64 + (part - 1) * 32 : rt * 128; c2 = part ? sp * 7 : 0;
      } else {
        const int p = i - 24;
        bar = bar_full2 + 8 * (p >> 1);
        bytes = W1_STAGE;
        dst = sb + piece_off(p);
        mp = (uint64_t)&maps.w2;
        c0 = (p >> 2) * 128 + (p & 1) * 64; c1 = sp * FC + ((p >> 1) & 1) * 112; c2 = 0;
      }
      *reinterpret_cast<uint4*>(smem + SM_TAB + i * 32) = make_uint4((uint32_t)mp, (uint32_t)(mp >> 32), dst, bar);
      *reinterpret_cast<uint4*>(smem + SM_TAB + i * 32 + 16) = make_uint4(c0, c1, c2, bytes);
    }
  }
  __syncthreads();
  if (threadIdx.x == 32 && blockIdx.x < 128) issue_items(smem, 0, 12);

  if (warp >= 8) {
    const int t = threadIdx.x & 127;
    const bool extra = blockIdx.x == 128;
    if (!extra) {
      const uint32_t stg = (uint32_t)(SM_WT + (warp - 8) * 2048);
      if (t < 16) {
        const size_t o = (size_t)(s0 + t) * DF_ + 256;
        g_wt[(size_t)256 * S_ + s0 + t] = (uint32_t)__ldg(reinterpret_cast<const unsigned short*>(wr) + o) |
                                          ((uint32_t)__ldg(reinterpret_cast<const unsigned short*>(wi) + o) << 16);
      }
      uint32_t wv[2][16];
      {
        const unsigned short* pr = reinterpret_cast<const unsigned short*>(wr) + (size_t)s0 * DF_ + t;
        const unsigned short* pi = reinterpret_cast<const unsigned short*>(wi) + (size_t)s0 * DF_ + t;
#pragma unroll
        for (int u = 0; u < 32; u++)
          wv[u >> 4][u & 15] = (uint32_t)__ldg(pr + (u & 15) * DF_ + (u >> 4) * 128) | ((uint32_t)__ldg(pi + (u & 15) * DF_ + (u >> 4) * 128) << 16);
      }
#pragma unroll
      for (int rd = 0; rd < 2; rd++) {
        if (rd && lane == 0) asm volatile("cp.async.bulk.wait_group.read 0;" ::: "memory");
        __syncwarp();
#pragma unroll
        for (int c = 0; c < 4; c++)
          *reinterpret_cast<uint4*>(smem + stg + lane * 64 + ((c ^ ((lane >> 1) & 3)) << 4)) =
              make_uint4(wv[rd][4 * c], wv[rd][4 * c + 1], wv[rd][4 * c + 2], wv[rd][4 * c + 3]);
        fence_async();
        __syncwarp();
        if (lane == 0) {
          tma_store_2d(&maps.wt, s0, rd * 128 + (warp - 8) * 32, sb + stg);
          asm volatile("cp.async.bulk.commit_group;" ::: "memory");
        }
      }
      if (lane == 0) { asm volatile("cp.async.bulk.wait_group 0;" ::: "memory"); __threadfence(); }
    }
    named_bar(3, 128);
    if (t == 0) {
      TS(11);
      if (!extra) {
        mbar_wait(bar_p1, 0);
        tma_store_2d(&maps.spec, s0, 0, sb + SM_FFT);
        tma_store_commit_wait();
      }
      TS(12);
      const unsigned target = grid_arrive(&g_bar[0]);
      grid_wait(&g_bar[0], target);
      mbar_arrive(bar_stats);
    }
    named_bar(3, 128);
    if (t == 0) TS(13);
    {
      float2* buf = reinterpret_cast<float2*>(tile);
      const int k1 = t >> 3, m2 = t & 7;
      const int c0 = extra ? 256 : blockIdx.x * 2, nc = extra ? 1 : 2;
      float2 vn[16];
      uint32_t wn[16];
#pragma unroll 1
      for (int c = -1; c < nc; c++) {
        uint32_t wq[16];
        if (c >= 0) {
#pragma unroll
          for (int i = 0; i < 16; i++) { buf[128 * i + t] = vn[i]; wq[i] = wn[i]; }
        }
        if (c + 1 < nc) {
#pragma unroll
          for (int i = 0; i < 16; i++) {
            vn[i] = __ldcg(g_spec + (size_t)(c0 + c + 1) * S_ + 128 * i + t);
            wn[i] = __ldcg(g_wt + (size_t)(c0 + c + 1) * S_ + 128 * i + t);
          }
        }
        if (c < 0) continue;
#pragma unroll 1
        for (int it = 0; it < 2; it++) {
#pragma unroll 1
          for (int p = 0; p < 2; p++) {
            const float2* in = buf + (p ? k1 * 136 + m2 : t);
            const int is = p ? 8 : 128;
            float2 v[16];
#pragma unroll
            for (int i = 0; i < 16; i++) v[i] = in[i * is];
            dft16<-1>(v);
            twiddle16(v, p ? 16 * m2 : t);
            named_bar(3, 128);
            float2* o = buf + (p ? k1 * 9 + m2 : t);
            const int os = p ? 144 : 136;
#pragma unroll
            for (int kk = 0; kk < 16; kk++) o[kk * os] = v[O16(kk)];
            named_bar(3, 128);
          }
          float2 e[2][8];
#pragma unroll
          for (int m = 0; m < 8; m++) { e[0][m] = buf[t * 9 + m]; e[1][m] = buf[(t + 128) * 9 + m]; }
          dft8<-1>(e[0]);
          dft8<-1>(e[1]);
          named_bar(3, 128);
          if (it == 0) {
            constexpr float SC = 1.0f / (2048.0f * 512.0f);
#pragma unroll
            for (int i = 0; i < 16; i++)
              buf[128 * i + t] = cconj(cmul(e[i & 1][O8(i >> 1)], make_float2(bflo(wq[i]) * SC, bfhi(wq[i]) * SC)));
          } else {
            float2* col = g_spec + (size_t)(c0 + c) * S_ + t;
#pragma unroll
            for (int i = 0; i < 16; i++) col[128 * i] = cconj(e[i & 1][O8(i >> 1)]);
          }
        }
      }
    }
    named_bar(3, 128);
    if (warp == 9 && lane < 8 && !extra) {
#pragma unroll 1
      for (int jq = 0; jq < NJOB; jq++) {
        mbar_wait(bar_st + 8 * jq, 0);
        __threadfence();
        atomicAdd(&g_flag[(rt * NJOB + jq) * 8 + lane], 1u);
      }
    }
    if (t == 64 && !extra) {
        mbar_wait(bar_st + 24, 0);
#pragma unroll 1
        for (int jq = 0; jq < NJOB; jq++) {
          unsigned* fl = &g_flag[(rt * NJOB + jq) * 8 + sp];
          int it = 0;
          while (ld_acquire(fl) < 8u) {
            if (++it > (1 << 22)) __trap();
          }
          *fl = 0u;
          fence_async();
          mbar_expect_tx(bar_g + 8 * jq, jq ? 32768 : 32768 + 17 * 1024);
          asm volatile("cp.async.bulk.shared::cluster.global.mbarrier::complete_tx::bytes [%0], [%1], %2, [%3];"
                       ::"r"(sb + jq * 32768), "l"(g_part + (((size_t)rt * NJOB + jq) * 8 + sp) * 8 * 256), "r"(32768), "r"(bar_g + 8 * jq) : "memory");
          if (jq == 0) {
#pragma unroll 1
            for (int i = 0; i < 17; i++)
              asm volatile("cp.async.bulk.shared::cluster.global.mbarrier::complete_tx::bytes [%0], [%1], %2, [%3];"
                           ::"r"(sb + 131072 + i * SPITCH * 4), "l"(i < 16 ? x + (size_t)(s0 + i) * D_ : b2), "r"(1024), "r"(bar_g) : "memory");
          }
        }
    }
    if (t == 0) {
      TS(14);
      const unsigned target = grid_arrive(&g_bar[1]);
      if (!extra) {
        grid_wait(&g_bar[1], target);
        TS(15);
        fence_async();
        mbar_expect_tx(bar_tile, 32768);
        tma_load_2d(sb + SM_FFT, &maps.spec, s0, 0, bar_tile);
      }
    }
  } else {
    if (blockIdx.x == 128) return;
    const int tid = threadIdx.x;
    const int r = tid & 15, q = tid >> 4;
#pragma unroll 1
    for (int ph = 0; ph < 3; ph++) {
      if (ph) {
        float y256 = 0.f;
        if (ph == 2) {
          mbar_wait(bar_tile, 0);
          if (tid == 0) TS(17);
          y256 = __ldcg(&g_spec[(size_t)256 * S_ + s0 + r]).x;
        }
        const float sg = ph == 1 ? -1.f : 1.f, sc = ph == 1 ? 0.5f : 1.f;
        float2 tw = twcs<512>(q);
#pragma unroll 4
        for (int i = 0; i < 8; i++) {
          const int j = q + 16 * i;
          float2* pa = tile_at(tile, j, r);
          float2* pb = tile_at(tile, j == 0 ? 128 : 256 - j, r);
          const float2 A = *pa, B = *pb;
          const float2 P = make_float2(sc * (A.x + B.x), sc * (A.y - B.y)), M = make_float2(sc * (A.x - B.x), sc * (A.y + B.y));
          const float ts = sg * tw.y;
          const float2 T = make_float2(M.x * tw.x - M.y * ts, M.y * tw.x + M.x * ts);
          tw = cmul(tw, make_float2(0.98078528040323044f, 0.19509032201612825f));
          const float2 V = make_float2(-sg * T.y, sg * T.x);
          if (j) {
            *pa = make_float2(P.x + V.x, -sg * (P.y + V.y));
            *pb = make_float2(P.x - V.x, sg * (P.y - V.y));
          } else if (ph == 1) {
            g_spec[(size_t)256 * S_ + s0 + r] = make_float2(A.x - A.y, 0.f);
            *pa = make_float2(A.x + A.y, 0.f);
            *pb = cconj(B);
          } else {
            *pa = make_float2(A.x + y256, y256 - A.x);
            *pb = make_float2(2.f * B.x, 2.f * B.y);
          }
        }
      }
      if (ph == 1) {
        fence_async();
        mbar_arrive(bar_p1);
        gemm_part(smem, maps, b1, rt, sp);
        continue;
      }
      if (ph == 0) {
        uint32_t w[16];
        const uint32_t* xw = reinterpret_cast<const uint32_t*>(x + (size_t)(s0 + q) * D_);
#pragma unroll
        for (int n1 = 0; n1 < 16; n1++) w[n1] = __ldg(xw + 16 * n1 + r);
        if ((tid & 127) < 112) {
          const uint32_t* pw = reinterpret_cast<const uint32_t*>(w1 + (size_t)(rt * 32 + (tid >> 7) * 16) * F_ + sp * FC) + (tid & 127);
          float c0 = 0.f, c1 = 0.f;
#pragma unroll
          for (int k = 0; k < 16; k++) { const uint32_t ww = __ldg(pw + k * (F_ / 2)); c0 += bflo(ww); c1 += bfhi(ww); }
          g_cs[(sp * 32 + rt * 2 + (tid >> 7)) * 112 + (tid & 127)] = make_float2(c0, c1);
        }
        float sum = 0.f;
#pragma unroll
        for (int n1 = 0; n1 < 16; n1++) sum += bflo(w[n1]) + bfhi(w[n1]);
#pragma unroll
        for (int o = 1; o < 16; o <<= 1) sum += __shfl_xor_sync(0xffffffffu, sum, o);
        const float mean = sum * (1.0f / D_);
        float sq = 0.f;
#pragma unroll
        for (int n1 = 0; n1 < 16; n1++) {
          float a = bflo(w[n1]) - mean, c = bfhi(w[n1]) - mean;
          sq += a * a + c * c;
        }
#pragma unroll
        for (int o = 1; o < 16; o <<= 1) sq += __shfl_xor_sync(0xffffffffu, sq, o);
        const uint32_t nm2 = pack_bf16(-mean, -mean);
        float sd, rs;
        asm("sqrt.approx.f32 %0, %1;" : "=f"(sd) : "f"(bf16r(bf16r(sq * (1.0f / D_)) + 1e-5f)));
        asm("rcp.approx.f32 %0, %1;" : "=f"(rs) : "f"(bf16r(sd)));
        if (r == 0) g_stats[s0 + q] = make_float2(-bflo(nm2), rs);
#pragma unroll
        for (int n1 = 0; n1 < 16; n1++) {
          const uint32_t d = hadd2_bf16(w[n1], nm2);
          const uint32_t xn = pack_bf16(bflo(d) * rs, bfhi(d) * rs);
          *tile_at(tile, 16 * n1 + r, q) = make_float2(bflo(xn), bfhi(xn));
        }
      }
      named_bar(1, 256);
      {
        uint8_t* pa = reinterpret_cast<uint8_t*>(tile_at(tile, q, r));
        const uint8_t* pb = tile + q * 2048 + (r & 1) * 8;
#pragma unroll 1
        for (int p = 0; p < 2; p++) {
          float2 v[16];
#pragma unroll
          for (int i = 0; i < 16; i++)
            v[i] = *reinterpret_cast<const float2*>(p ? pb + i * 128 + ((((r >> 1) ^ i) & 7) << 4) : pa + i * 2048);
          dft16<-1>(v);
          if (p == 0) twiddle16(v, 8 * q);
          named_bar(1, 256);
          if (p && ph) {
#pragma unroll
            for (int i = 0; i < 16; i++) reinterpret_cast<uint32_t*>(tile)[r * SPITCH + q + 16 * i] = pack_bf16(v[O16(i)].x, -v[O16(i)].y);
          } else {
#pragma unroll
            for (int i = 0; i < 16; i++) *reinterpret_cast<float2*>(pa + i * 2048) = v[O16(i)];
          }
          named_bar(1, 256);
        }
      }
      if (tid == 0 && ph == 0) TS(10);
    }
    if (tid == 0) TS(16);
    {
      const int g = lane >> 2;
      const uint32_t* stile = reinterpret_cast<const uint32_t*>(tile);
      const uint32_t* xs = reinterpret_cast<const uint32_t*>(smem + 131072);
#pragma unroll 1
      for (int jq = 0; jq < NJOB; jq++) {
        const int cw = jq * 64 + 8 * warp + (lane & 3);
        mbar_wait(bar_g + 8 * jq, 0);
        const uint4* src = reinterpret_cast<const uint4*>(smem + jq * 32768) + tid;
        float o[8];
#pragma unroll
        for (int c = 0; c < 8; c++) o[c] = 0.f;
#pragma unroll
        for (int s = 0; s < 8; s++) {
          const uint4 v = src[s * 256];
          o[0] += bflo(v.x); o[1] += bfhi(v.x); o[2] += bflo(v.y); o[3] += bfhi(v.y);
          o[4] += bflo(v.z); o[5] += bfhi(v.z); o[6] += bflo(v.w); o[7] += bfhi(v.w);
        }
#pragma unroll
        for (int c = 0; c < 4; c++) {
          const int row = g + 8 * (c & 1), w = cw + 4 * (c >> 1);
          const uint32_t sw = stile[row * SPITCH + w];
          const uint32_t p = hadd2_bf16(pack_bf16(0.5f * o[2 * c], 0.5f * o[2 * c + 1]), xs[16 * SPITCH + w]);
          const float oa = bflo(p), ob = bfhi(p);
          const uint32_t gg = pack_bf16(__fdividef(oa, 1.0f + __expf(-oa)), __fdividef(ob, 1.0f + __expf(-ob)));
          const uint32_t sg = pack_bf16(bflo(sw) * bflo(gg), bfhi(sw) * bfhi(gg));
          reinterpret_cast<uint32_t*>(out)[(size_t)(s0 + row) * 256 + w] = hadd2_bf16(xs[row * SPITCH + w], sg);
        }
        if (tid == 0) TS(20 + jq);
      }
    }
  }
}

typedef CUresult (*EncodeFn)(CUtensorMap*, CUtensorMapDataType, cuuint32_t, void*, const cuuint64_t*, const cuuint64_t*,
                             const cuuint32_t*, const cuuint32_t*, CUtensorMapInterleave, CUtensorMapSwizzle,
                             CUtensorMapL2promotion, CUtensorMapFloatOOBfill);

}

extern "C" void kernel_launch(void* const* d_in, const int* in_sizes, int n_in, void* d_out, int out_size) {
  const __nv_bfloat16* x = (const __nv_bfloat16*)d_in[0];
  const __nv_bfloat16* wr = (const __nv_bfloat16*)d_in[1];
  const __nv_bfloat16* wi = (const __nv_bfloat16*)d_in[2];
  const __nv_bfloat16* w1 = (const __nv_bfloat16*)d_in[4];
  const __nv_bfloat16* b1 = (const __nv_bfloat16*)d_in[5];
  const __nv_bfloat16* w2 = (const __nv_bfloat16*)d_in[6];
  const __nv_bfloat16* b2 = (const __nv_bfloat16*)d_in[7];
  __nv_bfloat16* out = (__nv_bfloat16*)d_out;

  static EncodeFn enc = nullptr;
  static void* p_spec = nullptr;
  static void* p_wt = nullptr;
  if (!enc) {
    void* fn = nullptr;
    cudaDriverEntryPointQueryResult qr;
    cudaGetDriverEntryPoint("cuTensorMapEncodeTiled", &fn, cudaEnableDefault, &qr);
    enc = (EncodeFn)fn;
    cudaFuncSetAttribute(k_mega, cudaFuncAttributeMaxDynamicSharedMemorySize, SM_TOTAL);
    cudaGetSymbolAddress(&p_spec, g_spec);
    cudaGetSymbolAddress(&p_wt, g_wt);
  }
  Maps m;
  const cuuint32_t es[3] = {1, 1, 1};
  {
    cuuint64_t dims[3] = {(cuuint64_t)D_, (cuuint64_t)S_, 1};
    cuuint64_t strides[2] = {(cuuint64_t)D_ * 2, (cuuint64_t)D_ * 2 * S_};
    cuuint32_t box[3] = {64, 128, 1};
    enc(&m.x, CU_TENSOR_MAP_DATA_TYPE_BFLOAT16, 3, (void*)x, dims, strides, box, es, CU_TENSOR_MAP_INTERLEAVE_NONE,
        CU_TENSOR_MAP_SWIZZLE_128B, CU_TENSOR_MAP_L2_PROMOTION_L2_128B, CU_TENSOR_MAP_FLOAT_OOB_FILL_NONE);
  }
  {
    cuuint64_t dims[3] = {32, 512, 56};
    cuuint64_t strides[2] = {(cuuint64_t)F_ * 2, 64};
    cuuint32_t box[3] = {32, 32, 7};
    enc(&m.w1, CU_TENSOR_MAP_DATA_TYPE_BFLOAT16, 3, (void*)w1, dims, strides, box, es, CU_TENSOR_MAP_INTERLEAVE_NONE,
        CU_TENSOR_MAP_SWIZZLE_64B, CU_TENSOR_MAP_L2_PROMOTION_L2_128B, CU_TENSOR_MAP_FLOAT_OOB_FILL_NONE);
  }
  {
    cuuint64_t dims[3] = {(cuuint64_t)D_, (cuuint64_t)F_, 1};
    cuuint64_t strides[2] = {(cuuint64_t)D_ * 2, (cuuint64_t)D_ * 2 * F_};
    cuuint32_t box[3] = {64, 112, 1};
    enc(&m.w2, CU_TENSOR_MAP_DATA_TYPE_BFLOAT16, 3, (void*)w2, dims, strides, box, es, CU_TENSOR_MAP_INTERLEAVE_NONE,
        CU_TENSOR_MAP_SWIZZLE_128B, CU_TENSOR_MAP_L2_PROMOTION_L2_128B, CU_TENSOR_MAP_FLOAT_OOB_FILL_NONE);
  }
  {
    cuuint64_t dims[2] = {(cuuint64_t)S_, 256};
    cuuint64_t strides[1] = {(cuuint64_t)S_ * 8};
    cuuint32_t box[2] = {16, 256};
    enc(&m.spec, CU_TENSOR_MAP_DATA_TYPE_FLOAT64, 2, p_spec, dims, strides, box, es, CU_TENSOR_MAP_INTERLEAVE_NONE,
        CU_TENSOR_MAP_SWIZZLE_128B, CU_TENSOR_MAP_L2_PROMOTION_NONE, CU_TENSOR_MAP_FLOAT_OOB_FILL_NONE);
  }
  {
    cuuint64_t dims[2] = {(cuuint64_t)S_, 257};
    cuuint64_t strides[1] = {(cuuint64_t)S_ * 4};
    cuuint32_t box[2] = {16, 32};
    enc(&m.wt, CU_TENSOR_MAP_DATA_TYPE_UINT32, 2, p_wt, dims, strides, box, es, CU_TENSOR_MAP_INTERLEAVE_NONE,
        CU_TENSOR_MAP_SWIZZLE_64B, CU_TENSOR_MAP_L2_PROMOTION_NONE, CU_TENSOR_MAP_FLOAT_OOB_FILL_NONE);
  }
  k_mega<<<129, NTHREADS, SM_TOTAL>>>(x, wr, wi, w1, b1, b2, out, m);
}
```

```cpp
#include <cuda_runtime.h>
#include <cuda_bf16.h>
#include <cuda.h>
#include <stdint.h>

namespace {

constexpr int S_ = 2048, D_ = 512, F_ = 1792, DF_ = 257;
constexpr int FC = 224;
constexpr int NJOB = 4;

__device__ __align__(1024) float2 g_spec[257 * 2048];
__device__ __align__(1024) uint32_t g_wt[257 * 2048];
__device__ uint4 g_part[16 * NJOB * 8 * 8 * 256];
__device__ float2 g_cs[8 * 32 * 112];
__device__ float2 g_stats[2048];
__device__ unsigned g_bar[2];
__device__ unsigned g_flag[16 * NJOB * 8];
#define TS(i)

__device__ __forceinline__ uint32_t smem_u32(const void* p) { return (uint32_t)__cvta_generic_to_shared(p); }
__device__ __forceinline__ float bf16r(float x) { return __bfloat162float(__float2bfloat16_rn(x)); }
__device__ __forceinline__ float bflo(uint32_t w) { return __uint_as_float(w << 16); }
__device__ __forceinline__ float bfhi(uint32_t w) { return __uint_as_float(w & 0xffff0000u); }
__device__ __forceinline__ uint32_t pack_bf16(float lo, float hi) {
  uint32_t r;
  asm("cvt.rn.bf16x2.f32 %0, %1, %2;" : "=r"(r) : "f"(hi), "f"(lo));
  return r;
}
__device__ __forceinline__ uint32_t hadd2_bf16(uint32_t a, uint32_t b) {
  uint32_t r;
  asm("add.rn.bf16x2 %0, %1, %2;" : "=r"(r) : "r"(a), "r"(b));
  return r;
}
__device__ __forceinline__ void named_bar(int id, int n) { asm volatile("bar.sync %0, %1;" ::"r"(id), "r"(n) : "memory"); }
__device__ __forceinline__ void fence_async() { asm volatile("fence.proxy.async;" ::: "memory"); }

__device__ __forceinline__ void mbar_init(uint32_t bar, int cnt) { asm volatile("mbarrier.init.shared::cta.b64 [%0], %1;" ::"r"(bar), "r"(cnt) : "memory"); }
__device__ __forceinline__ void mbar_expect_tx(uint32_t bar, uint32_t bytes) { asm volatile("mbarrier.arrive.expect_tx.shared::cta.b64 _, [%0], %1;" ::"r"(bar), "r"(bytes) : "memory"); }
__device__ __forceinline__ void mbar_arrive(uint32_t bar) { asm volatile("mbarrier.arrive.shared::cta.b64 _, [%0];" ::"r"(bar) : "memory"); }
__device__ __forceinline__ bool mbar_try(uint32_t bar, uint32_t parity) {
  uint32_t ok;
  asm volatile("{\n.reg .pred p;\nmbarrier.try_wait.parity.shared::cta.b64 p, [%1], %2, %3;\nselp.u32 %0, 1, 0, p;\n}\n" : "=r"(ok) : "r"(bar), "r"(parity), "r"(20000u) : "memory");
  return ok != 0;
}
__device__ __forceinline__ void mbar_wait(uint32_t bar, uint32_t parity) {
  int it = 0;
  while (!mbar_try(bar, parity)) {
    if (++it > (1 << 22)) __trap();
  }
}
__device__ __forceinline__ void tma_load_3d(uint32_t dst, const CUtensorMap* map, int c0, int c1, int c2, uint32_t bar) {
  asm volatile("cp.async.bulk.tensor.3d.shared::cluster.global.mbarrier::complete_tx::bytes [%0], [%1, {%3, %4, %5}], [%2];"
               ::"r"(dst), "l"((uint64_t)map), "r"(bar), "r"(c0), "r"(c1), "r"(c2) : "memory");
}
__device__ __forceinline__ void tma_load_2d(uint32_t dst, const CUtensorMap* map, int c0, int c1, uint32_t bar) {
  asm volatile("cp.async.bulk.tensor.2d.shared::cluster.global.mbarrier::complete_tx::bytes [%0], [%1, {%3, %4}], [%2];"
               ::"r"(dst), "l"((uint64_t)map), "r"(bar), "r"(c0), "r"(c1) : "memory");
}
__device__ __forceinline__ void tma_store_2d(const CUtensorMap* map, int c0, int c1, uint32_t src) {
  asm volatile("cp.async.bulk.tensor.2d.global.shared::cta.bulk_group [%0, {%2, %3}], [%1];"
               ::"l"((uint64_t)map), "r"(src), "r"(c0), "r"(c1) : "memory");
}
__device__ __forceinline__ void tma_store_commit_wait() {
  asm volatile("cp.async.bulk.commit_group;" ::: "memory");
  asm volatile("cp.async.bulk.wait_group 0;" ::: "memory");
}
__device__ __forceinline__ void wgmma_fence() { asm volatile("wgmma.fence.sync.aligned;" ::: "memory"); }
__device__ __forceinline__ void wgmma_commit() { asm volatile("wgmma.commit_group.sync.aligned;" ::: "memory"); }
template <int N> __device__ __forceinline__ void wgmma_wait() { asm volatile("wgmma.wait_group.sync.aligned %0;" ::"n"(N) : "memory"); }
__device__ __forceinline__ uint64_t make_desc(uint32_t addr, uint32_t lbo_bytes, uint32_t sbo_bytes, uint32_t swz) {
  uint64_t d = 0;
  d |= (uint64_t)((addr & 0x3FFFF) >> 4);
  d |= (uint64_t)((lbo_bytes & 0x3FFFF) >> 4) << 16;
  d |= (uint64_t)((sbo_bytes & 0x3FFFF) >> 4) << 32;
  d |= (uint64_t)swz << 62;
  return d;
}
__device__ __forceinline__ unsigned ld_acquire(const unsigned* p) {
  unsigned v;
  asm volatile("ld.acquire.gpu.global.u32 %0, [%1];" : "=r"(v) : "l"(p) : "memory");
  return v;
}

__device__ __forceinline__ void wgmma_n224_ss(float (&d)[112], uint64_t da, uint64_t db, int scale_d) {
  asm volatile("{\n.reg .pred p;\nsetp.ne.b32 p, %114, 0;\n"
    "wgmma.mma_async.sync.aligned.m64n224k16.f32.bf16.bf16 {%0, %1, %2, %3, %4, %5, %6, %7, %8, %9, %10, %11, %12, %13, %14, %15, %16, %17, %18, %19, %20, %21, %22, %23, %24, %25, %26, %27, %28, %29, %30, %31, %32, %33, %34, %35, %36, %37, %38, %39, %40, %41, %42, %43, %44, %45, %46, %47, %48, %49, %50, %51, %52, %53, %54, %55, %56, %57, %58, %59, %60, %61, %62, %63, %64, %65, %66, %67, %68, %69, %70, %71, %72, %73, %74, %75, %76, %77, %78, %79, %80, %81, %82, %83, %84, %85, %86, %87, %88, %89, %90, %91, %92, %93, %94, %95, %96, %97, %98, %99, %100, %101, %102, %103, %104, %105, %106, %107, %108, %109, %110, %111}, %112, %113, p, 1, 1, 0, 1;\n}\n"
    : "+f"(d[0]), "+f"(d[1]), "+f"(d[2]), "+f"(d[3]), "+f"(d[4]), "+f"(d[5]), "+f"(d[6]), "+f"(d[7]), "+f"(d[8]), "+f"(d[9]), "+f"(d[10]), "+f"(d[11]), "+f"(d[12]), "+f"(d[13]), "+f"(d[14]), "+f"(d[15]), "+f"(d[16]), "+f"(d[17]), "+f"(d[18]), "+f"(d[19]), "+f"(d[20]), "+f"(d[21]), "+f"(d[22]), "+f"(d[23]), "+f"(d[24]), "+f"(d[25]), "+f"(d[26]), "+f"(d[27]), "+f"(d[28]), "+f"(d[29]), "+f"(d[30]), "+f"(d[31]), "+f"(d[32]), "+f"(d[33]), "+f"(d[34]), "+f"(d[35]), "+f"(d[36]), "+f"(d[37]), "+f"(d[38]), "+f"(d[39]), "+f"(d[40]), "+f"(d[41]), "+f"(d[42]), "+f"(d[43]), "+f"(d[44]), "+f"(d[45]), "+f"(d[46]), "+f"(d[47]), "+f"(d[48]), "+f"(d[49]), "+f"(d[50]), "+f"(d[51]), "+f"(d[52]), "+f"(d[53]), "+f"(d[54]), "+f"(d[55]), "+f"(d[56]), "+f"(d[57]), "+f"(d[58]), "+f"(d[59]), "+f"(d[60]), "+f"(d[61]), "+f"(d[62]), "+f"(d[63]), "+f"(d[64]), "+f"(d[65]), "+f"(d[66]), "+f"(d[67]), "+f"(d[68]), "+f"(d[69]), "+f"(d[70]), "+f"(d[71]), "+f"(d[72]), "+f"(d[73]), "+f"(d[74]), "+f"(d[75]), "+f"(d[76]), "+f"(d[77]), "+f"(d[78]), "+f"(d[79]), "+f"(d[80]), "+f"(d[81]), "+f"(d[82]), "+f"(d[83]), "+f"(d[84]), "+f"(d[85]), "+f"(d[86]), "+f"(d[87]), "+f"(d[88]), "+f"(d[89]), "+f"(d[90]), "+f"(d[91]), "+f"(d[92]), "+f"(d[93]), "+f"(d[94]), "+f"(d[95]), "+f"(d[96]), "+f"(d[97]), "+f"(d[98]), "+f"(d[99]), "+f"(d[100]), "+f"(d[101]), "+f"(d[102]), "+f"(d[103]), "+f"(d[104]), "+f"(d[105]), "+f"(d[106]), "+f"(d[107]), "+f"(d[108]), "+f"(d[109]), "+f"(d[110]), "+f"(d[111])
    : "l"(da), "l"(db), "r"(scale_d));
}
__device__ __forceinline__ void wgmma_n128_rs(float (&d)[64], uint32_t a0, uint32_t a1, uint32_t a2, uint32_t a3, uint64_t db, int scale_d) {
  asm volatile("{\n.reg .pred p;\nsetp.ne.b32 p, %69, 0;\n"
    "wgmma.mma_async.sync.aligned.m64n128k16.f32.bf16.bf16 {%0, %1, %2, %3, %4, %5, %6, %7, %8, %9, %10, %11, %12, %13, %14, %15, %16, %17, %18, %19, %20, %21, %22, %23, %24, %25, %26, %27, %28, %29, %30, %31, %32, %33, %34, %35, %36, %37, %38, %39, %40, %41, %42, %43, %44, %45, %46, %47, %48, %49, %50, %51, %52, %53, %54, %55, %56, %57, %58, %59, %60, %61, %62, %63}, {%64, %65, %66, %67}, %68, p, 1, 1, 1;\n}\n"
    : "+f"(d[0]), "+f"(d[1]), "+f"(d[2]), "+f"(d[3]), "+f"(d[4]), "+f"(d[5]), "+f"(d[6]), "+f"(d[7]), "+f"(d[8]), "+f"(d[9]), "+f"(d[10]), "+f"(d[11]), "+f"(d[12]), "+f"(d[13]), "+f"(d[14]), "+f"(d[15]), "+f"(d[16]), "+f"(d[17]), "+f"(d[18]), "+f"(d[19]), "+f"(d[20]), "+f"(d[21]), "+f"(d[22]), "+f"(d[23]), "+f"(d[24]), "+f"(d[25]), "+f"(d[26]), "+f"(d[27]), "+f"(d[28]), "+f"(d[29]), "+f"(d[30]), "+f"(d[31]), "+f"(d[32]), "+f"(d[33]), "+f"(d[34]), "+f"(d[35]), "+f"(d[36]), "+f"(d[37]), "+f"(d[38]), "+f"(d[39]), "+f"(d[40]), "+f"(d[41]), "+f"(d[42]), "+f"(d[43]), "+f"(d[44]), "+f"(d[45]), "+f"(d[46]), "+f"(d[47]), "+f"(d[48]), "+f"(d[49]), "+f"(d[50]), "+f"(d[51]), "+f"(d[52]), "+f"(d[53]), "+f"(d[54]), "+f"(d[55]), "+f"(d[56]), "+f"(d[57]), "+f"(d[58]), "+f"(d[59]), "+f"(d[60]), "+f"(d[61]), "+f"(d[62]), "+f"(d[63])
    : "r"(a0), "r"(a1), "r"(a2), "r"(a3), "l"(db), "r"(scale_d));
}

__device__ __forceinline__ float2 cadd(float2 a, float2 b) { return make_float2(a.x + b.x, a.y + b.y); }
__device__ __forceinline__ float2 csub(float2 a, float2 b) { return make_float2(a.x - b.x, a.y - b.y); }
__device__ __forceinline__ float2 cmul(float2 a, float2 b) { return make_float2(a.x * b.x - a.y * b.y, a.x * b.y + a.y * b.x); }
__device__ __forceinline__ float2 cconj(float2 a) { return make_float2(a.x, -a.y); }

template <int DIR> __device__ __forceinline__ void dft4(float2& a0, float2& a1, float2& a2, float2& a3) {
  float2 t0 = cadd(a0, a2), t1 = csub(a0, a2), t2 = cadd(a1, a3), t3 = csub(a1, a3);
  float2 t3r = DIR < 0 ? make_float2(t3.y, -t3.x) : make_float2(-t3.y, t3.x);
  a0 = cadd(t0, t2); a2 = csub(t0, t2); a1 = cadd(t1, t3r); a3 = csub(t1, t3r);
}
template <int DIR> __device__ __forceinline__ float2 mulw(float2 v, float c, float s) {
  return DIR < 0 ? make_float2(v.x * c + v.y * s, v.y * c - v.x * s) : make_float2(v.x * c - v.y * s, v.y * c + v.x * s);
}
template <int DIR> __device__ __forceinline__ float2 muli(float2 v) {
  return DIR < 0 ? make_float2(v.y, -v.x) : make_float2(-v.y, v.x);
}
#define O16(k) (4 * ((k) & 3) + ((k) >> 2))
#define O8(k) (2 * ((k) & 3) + ((k) >> 2))
template <int DIR> __device__ __forceinline__ void dft16(float2 (&v)[16]) {
  constexpr float C1 = 0.92387953251128674f, S1 = 0.38268343236508977f, R = 0.70710678118654752f;
#pragma unroll
  for (int n2 = 0; n2 < 4; n2++) dft4<DIR>(v[n2], v[4 + n2], v[8 + n2], v[12 + n2]);
  v[5] = mulw<DIR>(v[5], C1, S1);
  v[6] = mulw<DIR>(v[6], R, R);
  v[7] = mulw<DIR>(v[7], S1, C1);
  v[9] = mulw<DIR>(v[9], R, R);
  v[10] = muli<DIR>(v[10]);
  v[11] = mulw<DIR>(v[11], -R, R);
  v[13] = mulw<DIR>(v[13], S1, C1);
  v[14] = mulw<DIR>(v[14], -R, R);
  v[15] = mulw<DIR>(v[15], -C1, -S1);
#pragma unroll
  for (int k1 = 0; k1 < 4; k1++) dft4<DIR>(v[4 * k1], v[4 * k1 + 1], v[4 * k1 + 2], v[4 * k1 + 3]);
}
template <int DIR> __device__ __forceinline__ void dft8(float2 (&v)[8]) {
  constexpr float R = 0.70710678118654752f;
  dft4<DIR>(v[0], v[2], v[4], v[6]);
  dft4<DIR>(v[1], v[3], v[5], v[7]);
  v[3] = mulw<DIR>(v[3], R, R);
  v[5] = muli<DIR>(v[5]);
  v[7] = mulw<DIR>(v[7], -R, R);
#pragma unroll
  for (int k1 = 0; k1 < 4; k1++) {
    float2 a = v[2 * k1], b = v[2 * k1 + 1];
    v[2 * k1] = cadd(a, b); v[2 * k1 + 1] = csub(a, b);
  }
}
template <int N> __device__ __forceinline__ float2 twcs(int m) {
  m &= (N - 1);
  if (m >= N / 2) m -= N;
  float s, c;
  __sincosf((float)m * (6.283185307179586f / N), &s, &c);
  return make_float2(c, s);
}

__device__ __forceinline__ void twiddle16(float2 (&v)[16], int m) {
  const float2 w1 = twcs<2048>(m);
  float2 w = w1;
#pragma unroll
  for (int k = 1; k < 16; k++) {
    v[O16(k)] = mulw<-1>(v[O16(k)], w.x, w.y);
    if (k < 15) w = cmul(w, w1);
  }
}
__device__ __forceinline__ float2* tile_at(uint8_t* tile, int k, int r) {
  return reinterpret_cast<float2*>(tile + k * 128 + ((((r >> 1) ^ k) & 7) << 4) + (r & 1) * 8);
}
constexpr int SPITCH = 260;

constexpr int STEP = 45056;
constexpr int W1_STAGE = 14336;
constexpr int SM_FFT = 184 * 1024;
constexpr int SM_WT = SM_FFT + 32768;
constexpr int SM_BAR = SM_WT + 8192;
constexpr int SM_TAB = SM_BAR + 256;
constexpr int SM_TOTAL = SM_TAB + 1280;
constexpr int NTHREADS = 384;

__device__ __forceinline__ float gelu2(float x) {
  float u = x * (0.7978845608028654f + 0.035677408136300125f * x * x);
  float th;
  asm("tanh.approx.f32 %0, %1;" : "=f"(th) : "f"(u));
  return fmaf(x, th, x);
}
__device__ __forceinline__ unsigned grid_arrive(unsigned* cnt) {
  __threadfence();
  unsigned old = atomicAdd(cnt, 1u);
  return (old / 129u + 1u) * 129u;
}
__device__ __forceinline__ void grid_wait(const unsigned* cnt, unsigned target) {
  int it = 0;
  while ((int)(ld_acquire(cnt) - target) < 0) {
    if (++it > (1 << 22)) __trap();
  }
}
__device__ __forceinline__ uint32_t piece_off(int p) {
  if (p >= 12) p -= 12;
  const int s = (p * 11) >> 5;
  return (uint32_t)(s * STEP + (p - 3 * s) * W1_STAGE);
}

struct Maps { CUtensorMap x, w1, w2, spec, wt; };

__device__ __forceinline__ void issue_items(const uint8_t* smem, int first, int n) {
#pragma unroll 1
  for (int i = first; i < first + n; i++) {
    const uint4 a = *reinterpret_cast<const uint4*>(smem + SM_TAB + i * 32);
    const uint4 c = *reinterpret_cast<const uint4*>(smem + SM_TAB + i * 32 + 16);
    if (c.w) mbar_expect_tx(a.w, c.w);
    tma_load_3d(a.z, reinterpret_cast<const CUtensorMap*>((uint64_t)a.x | ((uint64_t)a.y << 32)), (int)c.x, (int)c.y, (int)c.z, a.w);
  }
}

__device__ __forceinline__ void gemm_part(uint8_t* smem, const Maps& maps, const __nv_bfloat16* __restrict__ b1, int rt, int sp) {
  const uint32_t sb = smem_u32(smem);
  const int tid = threadIdx.x, warp = tid >> 5, lane = tid & 31, wg = warp >> 2;
  const uint32_t bar_full1 = sb + SM_BAR, bar_full2 = sb + SM_BAR + 64;
  unsigned* relcnt = reinterpret_cast<unsigned*>(smem + SM_BAR + 128);
  const uint32_t bar_stats = sb + SM_BAR + 160, bar_st = sb + SM_BAR + 224;
  uint32_t ha[56];
      auto release = [&](int j) {
        __syncwarp();
        if (lane == 0) {
          __threadfence_block();
          if ((atomicAdd(&relcnt[j & 3], 1u) & 7u) == 7u) {
            __threadfence_block();
            issue_items(smem, 3 * j + 12, 3);
          }
        }
      };
      {
        float acc[112];
#pragma unroll
        for (int i = 0; i < 112; i++) acc[i] = 0.f;
        const uint64_t dA = make_desc(sb + __shfl_sync(0xffffffffu, wg, 0) * 8192, 16, 1024, 1), dB = make_desc(sb + 16384, 2048, 512, 2);
#pragma unroll 1
        for (int j = 0; j < 8; j++) {
          const uint32_t base = (j & 3) * STEP;
          mbar_wait(bar_full1 + 8 * (j & 3), j >> 2);
          if (tid == 0) TS(24 + j);
          wgmma_fence();
#pragma unroll
          for (int kk = 0; kk < 4; kk++)
            wgmma_n224_ss(acc, dA + ((base + kk * 32) >> 4), dB + ((base + (kk >> 1) * W1_STAGE + (kk & 1) * 1024) >> 4), 1);
          wgmma_commit();
          if (j > 0) {
            wgmma_wait<1>();
            release(j - 1);
          }
        }
        mbar_wait(bar_stats, 0);
        if (tid < 224) {
          float c0 = 0.f, c1 = 0.f;
          const float2* pc = g_cs + (sp * 32 + (tid & 1) * 16) * 112 + (tid >> 1);
#pragma unroll
          for (int i = 0; i < 16; i++) { const float2 c = __ldcg(pc + i * 112); c0 += c.x; c1 += c.y; }
          c0 += __shfl_xor_sync(0xffffffffu, c0, 1); c1 += __shfl_xor_sync(0xffffffffu, c1, 1);
          const uint32_t bw = __ldg(reinterpret_cast<const uint32_t*>(b1 + sp * FC) + (tid >> 1));
          reinterpret_cast<float4*>(smem + SM_WT)[tid >> 1] = make_float4(c0, c1, bflo(bw), bfhi(bw));
        }
        const int row = rt * 128 + warp * 16 + (lane >> 2);
        const float2 st0 = __ldcg(&g_stats[row]), st1 = __ldcg(&g_stats[row + 8]);
        wgmma_wait<0>();
        if (tid == 0) TS(2);
        named_bar(1, 256);
        if (tid == 0) {
          issue_items(smem, 33, 3);
        }
        if (tid == 0) TS(3);
        const float4* csb = reinterpret_cast<const float4*>(smem + SM_WT) + (lane & 3);
#pragma unroll
        for (int j = 0; j < 28; j++) {
          const float4 c = csb[j * 4];
          ha[2 * j] = pack_bf16(gelu2(fmaf(fmaf(-st0.x, c.x, acc[4 * j]), st0.y, c.z)), gelu2(fmaf(fmaf(-st0.x, c.y, acc[4 * j + 1]), st0.y, c.w)));
          ha[2 * j + 1] = pack_bf16(gelu2(fmaf(fmaf(-st1.x, c.x, acc[4 * j + 2]), st1.y, c.z)), gelu2(fmaf(fmaf(-st1.x, c.y, acc[4 * j + 3]), st1.y, c.w)));
        }
      }
      if (tid == 0) TS(4);
      if (wg == 1) named_bar(2, 256);
#pragma unroll 1
      for (int jq = 0; jq < NJOB; jq++) {
        float acc[64];
#pragma unroll
        for (int h = 0; h < 2; h++) {
          const uint32_t o0 = piece_off(4 * jq + 2 * h), o1 = piece_off(4 * jq + 2 * h + 1);
          const uint64_t dW = make_desc(sb + o0, o1 - o0, 1024, 1);
          mbar_wait(bar_full2 + 8 * (2 * jq + h), 0);
          wgmma_fence();
#pragma unroll
          for (int kk = 0; kk < 7; kk++) {
            const int kb = h * 7 + kk;
            wgmma_n128_rs(acc, ha[4 * kb], ha[4 * kb + 1], ha[4 * kb + 2], ha[4 * kb + 3], dW + kk * 128, kb > 0);
          }
          wgmma_commit();
        }
        if (jq == 0 && wg == 0) asm volatile("bar.arrive 2, 256;" ::: "memory");
        wgmma_wait<0>();
        if (jq == 0 && lane == 0) {
          __threadfence_block();
          if (atomicAdd(&relcnt[4], 1u) == 7u) {
            __threadfence_block();
            issue_items(smem, 36, 4);
          }
        }
        uint4* dstp = g_part + ((((size_t)rt * NJOB + jq) * 8 + warp) * 8 + sp) * 256 + lane;
#pragma unroll
        for (int i = 0; i < 8; i++)
          dstp[i * 32] = make_uint4(pack_bf16(acc[8 * i], acc[8 * i + 1]), pack_bf16(acc[8 * i + 2], acc[8 * i + 3]),
                                    pack_bf16(acc[8 * i + 4], acc[8 * i + 5]), pack_bf16(acc[8 * i + 6], acc[8 * i + 7]));
        __syncwarp();
        if (lane == 0) mbar_arrive(bar_st + 8 * jq);
        if (tid == 0) TS(5 + jq);
      }
}

__global__ void __launch_bounds__(NTHREADS, 1)
k_mega(const __nv_bfloat16* __restrict__ x, const __nv_bfloat16* __restrict__ wr, const __nv_bfloat16* __restrict__ wi,
       const __nv_bfloat16* __restrict__ w1, const __nv_bfloat16* __restrict__ b1, const __nv_bfloat16* __restrict__ b2, __nv_bfloat16* __restrict__ out,
       const __grid_constant__ Maps maps) {
  extern __shared__ __align__(1024) uint8_t smem[];
  const uint32_t sb = smem_u32(smem);
  const int rt = blockIdx.x >> 3, sp = blockIdx.x & 7;
  const int warp = threadIdx.x >> 5, lane = threadIdx.x & 31;
  const int s0 = blockIdx.x * 16;
  if (threadIdx.x == 0) TS(0);
  const uint32_t bar_full1 = sb + SM_BAR;
  const uint32_t bar_full2 = sb + SM_BAR + 64;
  unsigned* relcnt = reinterpret_cast<unsigned*>(smem + SM_BAR + 128);
  const uint32_t bar_stats = sb + SM_BAR + 160;
  const uint32_t bar_p1 = sb + SM_BAR + 168;
  const uint32_t bar_tile = sb + SM_BAR + 176;
  const uint32_t bar_st = sb + SM_BAR + 224;
  const uint32_t bar_g = sb + SM_BAR + 192;
  uint8_t* tile = smem + SM_FFT;

  if (threadIdx.x == 0) {
    for (int i = 0; i < 4; i++) mbar_init(bar_full1 + 8 * i, 1);
    for (int i = 0; i < 8; i++) mbar_init(bar_full2 + 8 * i, 2);
    mbar_init(bar_stats, 1); mbar_init(bar_p1, 256); mbar_init(bar_tile, 1);
    for (int i = 0; i < 4; i++) { mbar_init(bar_g + 8 * i, 1); mbar_init(bar_st + 8 * i, 8); }
    for (int i = 0; i < 5; i++) relcnt[i] = 0;
    asm volatile("fence.mbarrier_init.release.cluster;" ::: "memory");
  }
  if (warp == 1) {
#pragma unroll 1
    for (int i = lane; i < 40; i += 32) {
      uint64_t mp; uint32_t dst, bar, bytes; int c0, c1, c2;
      if (i < 24) {
        const int j = (i * 11) >> 5, part = i - 3 * j;
        bar = bar_full1 + 8 * (j & 3);
        bytes = part ? 0 : STEP;
        dst = sb + (j & 3) * STEP + (part ? 16384 + (part - 1) * W1_STAGE : 0);
        mp = (uint64_t)(part ? &maps.w1 : &maps.x);
        c0 = part ? 0 : j * 64; c1 = part ? j * 64 + (part - 1) * 32 : rt * 128; c2 = part ? sp * 7 : 0;
      } else {
        const int p = i - 24;
        bar = bar_full2 + 8 * (p >> 1);
        bytes = W1_STAGE;
        dst = sb + piece_off(p);
        mp = (uint64_t)&maps.w2;
        c0 = (p >> 2) * 128 + (p & 1) * 64; c1 = sp * FC + ((p >> 1) & 1) * 112; c2 = 0;
      }
      *reinterpret_cast<uint4*>(smem + SM_TAB + i * 32) = make_uint4((uint32_t)mp, (uint32_t)(mp >> 32), dst, bar);
      *reinterpret_cast<uint4*>(smem + SM_TAB + i * 32 + 16) = make_uint4(c0, c1, c2, bytes);
    }
  }
  __syncthreads();
  if (threadIdx.x == 32 && blockIdx.x < 128) issue_items(smem, 0, 12);

  const bool cons = warp < 8;
  const bool extra = blockIdx.x == 128;
  if (cons && extra) return;
  const int tid = threadIdx.x, t = tid & 127;
  const int r = tid & 15, q = tid >> 4;
  const int k1 = t >> 3, m2 = t & 7;
  const int barid = cons ? 1 : 3, nthr = cons ? 256 : 128;
  float2* buf = reinterpret_cast<float2*>(tile);
  const int c0 = extra ? 256 : blockIdx.x * 2;
  float2 vn[16];
  uint32_t wn[16], wq[16];

  if (!cons) {
    if (!extra) {
      const uint32_t stg = (uint32_t)(SM_WT + (warp - 8) * 2048);
      if (t < 16) {
        const size_t o = (size_t)(s0 + t) * DF_ + 256;
        g_wt[(size_t)256 * S_ + s0 + t] = (uint32_t)__ldg(reinterpret_cast<const unsigned short*>(wr) + o) |
                                          ((uint32_t)__ldg(reinterpret_cast<const unsigned short*>(wi) + o) << 16);
      }
      const unsigned short* pr = reinterpret_cast<const unsigned short*>(wr) + (size_t)s0 * DF_ + t;
      const unsigned short* pi = reinterpret_cast<const unsigned short*>(wi) + (size_t)s0 * DF_ + t;
#pragma unroll
      for (int u = 0; u < 16; u++) {
        wq[u] = (uint32_t)__ldg(pr + u * DF_) | ((uint32_t)__ldg(pi + u * DF_) << 16);
        wn[u] = (uint32_t)__ldg(pr + u * DF_ + 128) | ((uint32_t)__ldg(pi + u * DF_ + 128) << 16);
      }
#pragma unroll
      for (int rd = 0; rd < 2; rd++) {
        if (rd && lane == 0) asm volatile("cp.async.bulk.wait_group.read 0;" ::: "memory");
        __syncwarp();
#pragma unroll
        for (int c = 0; c < 4; c++)
          *reinterpret_cast<uint4*>(smem + stg + lane * 64 + ((c ^ ((lane >> 1) & 3)) << 4)) =
              rd ? make_uint4(wn[4 * c], wn[4 * c + 1], wn[4 * c + 2], wn[4 * c + 3]) : make_uint4(wq[4 * c], wq[4 * c + 1], wq[4 * c + 2], wq[4 * c + 3]);
        fence_async();
        __syncwarp();
        if (lane == 0) {
          tma_store_2d(&maps.wt, s0, rd * 128 + (warp - 8) * 32, sb + stg);
          asm volatile("cp.async.bulk.commit_group;" ::: "memory");
        }
      }
      if (lane == 0) { asm volatile("cp.async.bulk.wait_group 0;" ::: "memory"); __threadfence(); }
    }
    named_bar(3, 128);
    if (t == 0) {
      TS(11);
      if (!extra) {
        mbar_wait(bar_p1, 0);
        tma_store_2d(&maps.spec, s0, 0, sb + SM_FFT);
        tma_store_commit_wait();
      }
      TS(12);
      const unsigned target = grid_arrive(&g_bar[0]);
      grid_wait(&g_bar[0], target);
      mbar_arrive(bar_stats);
    }
    named_bar(3, 128);
    if (t == 0) TS(13);
  }

  const int nst = cons ? 5 : (extra ? 4 : 8);
#pragma unroll 1
  for (int st = 0; st < nst; st++) {
    if (cons) {
      if (st >= 2 && st < 4) {
        float y256 = 0.f;
        if (st == 3) {
          mbar_wait(bar_tile, 0);
          if (tid == 0) TS(17);
          y256 = __ldcg(&g_spec[(size_t)256 * S_ + s0 + r]).x;
        }
        const float sg = st == 2 ? -1.f : 1.f, sc = st == 2 ? 0.5f : 1.f;
        float2 tw = twcs<512>(q);
#pragma unroll 2
        for (int i = 0; i < 8; i++) {
          const int j = q + 16 * i;
          float2* pa = tile_at(tile, j, r);
          float2* pb = tile_at(tile, j == 0 ? 128 : 256 - j, r);
          const float2 A = *pa, B = *pb;
          const float2 P = make_float2(sc * (A.x + B.x), sc * (A.y - B.y)), M = make_float2(sc * (A.x - B.x), sc * (A.y + B.y));
          const float ts = sg * tw.y;
          const float2 T = make_float2(M.x * tw.x - M.y * ts, M.y * tw.x + M.x * ts);
          tw = cmul(tw, make_float2(0.98078528040323044f, 0.19509032201612825f));
          const float2 V = make_float2(-sg * T.y, sg * T.x);
          if (j) {
            *pa = make_float2(P.x + V.x, -sg * (P.y + V.y));
            *pb = make_float2(P.x - V.x, sg * (P.y - V.y));
          } else if (st == 2) {
            g_spec[(size_t)256 * S_ + s0 + r] = make_float2(A.x - A.y, 0.f);
            *pa = make_float2(A.x + A.y, 0.f);
            *pb = cconj(B);
          } else {
            *pa = make_float2(A.x + y256, y256 - A.x);
            *pb = make_float2(2.f * B.x, 2.f * B.y);
          }
        }
      }
      if (st == 2) {
        fence_async();
        mbar_arrive(bar_p1);
        gemm_part(smem, maps, b1, rt, sp);
        continue;
      }
      if (st == 0) {
        uint32_t w[16];
        const uint32_t* xw = reinterpret_cast<const uint32_t*>(x + (size_t)(s0 + q) * D_);
#pragma unroll
        for (int n1 = 0; n1 < 16; n1++) w[n1] = __ldg(xw + 16 * n1 + r);
        if (t < 112) {
          const uint32_t* pw = reinterpret_cast<const uint32_t*>(w1 + (size_t)(rt * 32 + (tid >> 7) * 16) * F_ + sp * FC) + t;
          float a0 = 0.f, a1 = 0.f;
#pragma unroll
          for (int k = 0; k < 16; k++) { const uint32_t ww = __ldg(pw + k * (F_ / 2)); a0 += bflo(ww); a1 += bfhi(ww); }
          g_cs[(sp * 32 + rt * 2 + (tid >> 7)) * 112 + t] = make_float2(a0, a1);
        }
        float sum = 0.f;
#pragma unroll
        for (int n1 = 0; n1 < 16; n1++) sum += bflo(w[n1]) + bfhi(w[n1]);
#pragma unroll
        for (int o = 1; o < 16; o <<= 1) sum += __shfl_xor_sync(0xffffffffu, sum, o);
        const float mean = sum * (1.0f / D_);
        float sq = 0.f;
#pragma unroll
        for (int n1 = 0; n1 < 16; n1++) {
          float a = bflo(w[n1]) - mean, c = bfhi(w[n1]) - mean;
          sq += a * a + c * c;
        }
#pragma unroll
        for (int o = 1; o < 16; o <<= 1) sq += __shfl_xor_sync(0xffffffffu, sq, o);
        const uint32_t nm2 = pack_bf16(-mean, -mean);
        float sd, rs;
        asm("sqrt.approx.f32 %0, %1;" : "=f"(sd) : "f"(bf16r(bf16r(sq * (1.0f / D_)) + 1e-5f)));
        asm("rcp.approx.f32 %0, %1;" : "=f"(rs) : "f"(bf16r(sd)));
        if (r == 0) g_stats[s0 + q] = make_float2(-bflo(nm2), rs);
#pragma unroll
        for (int n1 = 0; n1 < 16; n1++) {
          const uint32_t d = hadd2_bf16(w[n1], nm2);
          const uint32_t xn = pack_bf16(bflo(d) * rs, bfhi(d) * rs);
          *tile_at(tile, 16 * n1 + r, q) = make_float2(bflo(xn), bfhi(xn));
        }
      }
      if (st == 0 || st == 3) named_bar(1, 256);
    } else if ((st & 3) == 0) {
#pragma unroll 1
      for (int c = (st ? 1 : 0); c < 2; c++) {
        if (c == 1) {
#pragma unroll
          for (int i = 0; i < 16; i++) { buf[128 * i + t] = vn[i]; wq[i] = wn[i]; }
        }
        if (st == 0) {
          const int cc = extra ? c0 : c0 + c;
#pragma unroll
          for (int i = 0; i < 16; i++) {
            vn[i] = __ldcg(g_spec + (size_t)cc * S_ + 128 * i + t);
            wn[i] = __ldcg(g_wt + (size_t)cc * S_ + 128 * i + t);
          }
        }
      }
    }
    {
      const int p = cons ? (st == 1 || st == 4) : (st & 1);
      uint8_t* ta = reinterpret_cast<uint8_t*>(tile_at(tile, q, r));
      const uint8_t* in = cons ? (p ? tile + q * 2048 + (r & 1) * 8 : ta) : tile + (p ? k1 * 136 + m2 : t) * 8;
      const int is = cons ? (p ? 128 : 2048) : (p ? 64 : 1024);
      const int xs = (cons && p) ? 16 : 0;
      float2 v[16];
#pragma unroll
      for (int i = 0; i < 16; i++) v[i] = *reinterpret_cast<const float2*>(in + i * is + (((r >> 1) ^ i) & 7) * xs);
      dft16<-1>(v);
      if (!cons || !p) twiddle16(v, cons ? 8 * q : (p ? 16 * m2 : t));
      named_bar(barid, nthr);
      if (cons && st == 4) {
#pragma unroll
        for (int i = 0; i < 16; i++) reinterpret_cast<uint32_t*>(tile)[r * SPITCH + q + 16 * i] = pack_bf16(v[O16(i)].x, -v[O16(i)].y);
      } else {
        uint8_t* o = cons ? ta : tile + (p ? k1 * 9 + m2 : t) * 8;
        const int os = cons ? 2048 : (p ? 144 * 8 : 136 * 8);
#pragma unroll
        for (int i = 0; i < 16; i++) *reinterpret_cast<float2*>(o + i * os) = v[O16(i)];
      }
      named_bar(barid, nthr);
      if (tid == 0 && st == 1) TS(10);
    }
    if (!cons && (st & 1)) {
      float2 e[2][8];
#pragma unroll
      for (int m = 0; m < 8; m++) { e[0][m] = buf[t * 9 + m]; e[1][m] = buf[(t + 128) * 9 + m]; }
      dft8<-1>(e[0]);
      dft8<-1>(e[1]);
      named_bar(3, 128);
      if (!(st & 2)) {
        constexpr float SC = 1.0f / (2048.0f * 512.0f);
#pragma unroll
        for (int i = 0; i < 16; i++)
          buf[128 * i + t] = cconj(cmul(e[i & 1][O8(i >> 1)], make_float2(bflo(wq[i]) * SC, bfhi(wq[i]) * SC)));
      } else {
        float2* col = g_spec + (size_t)(c0 + (st >> 2)) * S_ + t;
#pragma unroll
        for (int i = 0; i < 16; i++) col[128 * i] = cconj(e[i & 1][O8(i >> 1)]);
      }
    }
  }

  if (!cons) {
    named_bar(3, 128);
    if (warp == 9 && lane < 8 && !extra) {
#pragma unroll 1
      for (int jq = 0; jq < NJOB; jq++) {
        mbar_wait(bar_st + 8 * jq, 0);
        __threadfence();
        atomicAdd(&g_flag[(rt * NJOB + jq) * 8 + lane], 1u);
      }
    }
    if (t == 64 && !extra) {
      mbar_wait(bar_st + 24, 0);
#pragma unroll 1
      for (int jq = 0; jq < NJOB; jq++) {
        unsigned* fl = &g_flag[(rt * NJOB + jq) * 8 + sp];
        int it = 0;
        while (ld_acquire(fl) < 8u) {
          if (++it > (1 << 22)) __trap();
        }
        *fl = 0u;
        fence_async();
        mbar_expect_tx(bar_g + 8 * jq, jq ? 32768 : 32768 + 17 * 1024);
        asm volatile("cp.async.bulk.shared::cluster.global.mbarrier::complete_tx::bytes [%0], [%1], %2, [%3];"
                     ::"r"(sb + jq * 32768), "l"(g_part + (((size_t)rt * NJOB + jq) * 8 + sp) * 8 * 256), "r"(32768), "r"(bar_g + 8 * jq) : "memory");
        if (jq == 0) {
#pragma unroll 1
          for (int i = 0; i < 17; i++)
            asm volatile("cp.async.bulk.shared::cluster.global.mbarrier::complete_tx::bytes [%0], [%1], %2, [%3];"
                         ::"r"(sb + 131072 + i * SPITCH * 4), "l"(i < 16 ? x + (size_t)(s0 + i) * D_ : b2), "r"(1024), "r"(bar_g) : "memory");
        }
      }
    }
    if (t == 0) {
      TS(14);
      const unsigned target = grid_arrive(&g_bar[1]);
      if (!extra) {
        grid_wait(&g_bar[1], target);
        TS(15);
        fence_async();
        mbar_expect_tx(bar_tile, 32768);
        tma_load_2d(sb + SM_FFT, &maps.spec, s0, 0, bar_tile);
      }
    }
  } else {
    if (tid == 0) TS(16);
    const int g = lane >> 2;
    const uint32_t* stile = reinterpret_cast<const uint32_t*>(tile);
    const uint32_t* xs = reinterpret_cast<const uint32_t*>(smem + 131072);
#pragma unroll 1
    for (int jq = 0; jq < NJOB; jq++) {
      const int cw = jq * 64 + 8 * warp + (lane & 3);
      mbar_wait(bar_g + 8 * jq, 0);
      const uint4* src = reinterpret_cast<const uint4*>(smem + jq * 32768) + tid;
      float o[8];
#pragma unroll
      for (int c = 0; c < 8; c++) o[c] = 0.f;
#pragma unroll
      for (int s = 0; s < 8; s++) {
        const uint4 v = src[s * 256];
        o[0] += bflo(v.x); o[1] += bfhi(v.x); o[2] += bflo(v.y); o[3] += bfhi(v.y);
        o[4] += bflo(v.z); o[5] += bfhi(v.z); o[6] += bflo(v.w); o[7] += bfhi(v.w);
      }
#pragma unroll
      for (int c = 0; c < 4; c++) {
        const int row = g + 8 * (c & 1), w = cw + 4 * (c >> 1);
        const uint32_t sw = stile[row * SPITCH + w];
        const uint32_t p = hadd2_bf16(pack_bf16(0.5f * o[2 * c], 0.5f * o[2 * c + 1]), xs[16 * SPITCH + w]);
        const float oa = bflo(p), ob = bfhi(p);
        const uint32_t gg = pack_bf16(__fdividef(oa, 1.0f + __expf(-oa)), __fdividef(ob, 1.0f + __expf(-ob)));
        const uint32_t sg = pack_bf16(bflo(sw) * bflo(gg), bfhi(sw) * bfhi(gg));
        reinterpret_cast<uint32_t*>(out)[(size_t)(s0 + row) * 256 + w] = hadd2_bf16(xs[row * SPITCH + w], sg);
      }
      if (tid == 0) TS(20 + jq);
    }
  }
}

typedef CUresult (*EncodeFn)(CUtensorMap*, CUtensorMapDataType, cuuint32_t, void*, const cuuint64_t*, const cuuint64_t*,
                             const cuuint32_t*, const cuuint32_t*, CUtensorMapInterleave, CUtensorMapSwizzle,
                             CUtensorMapL2promotion, CUtensorMapFloatOOBfill);

}

extern "C" void kernel_launch(void* const* d_in, const int* in_sizes, int n_in, void* d_out, int out_size) {
  const __nv_bfloat16* x = (const __nv_bfloat16*)d_in[0];
  const __nv_bfloat16* wr = (const __nv_bfloat16*)d_in[1];
  const __nv_bfloat16* wi = (const __nv_bfloat16*)d_in[2];
  const __nv_bfloat16* w1 = (const __nv_bfloat16*)d_in[4];
  const __nv_bfloat16* b1 = (const __nv_bfloat16*)d_in[5];
  const __nv_bfloat16* w2 = (const __nv_bfloat16*)d_in[6];
  const __nv_bfloat16* b2 = (const __nv_bfloat16*)d_in[7];
  __nv_bfloat16* out = (__nv_bfloat16*)d_out;

  static EncodeFn enc = nullptr;
  static void* p_spec = nullptr;
  static void* p_wt = nullptr;
  if (!enc) {
    void* fn = nullptr;
    cudaDriverEntryPointQueryResult qr;
    cudaGetDriverEntryPoint("cuTensorMapEncodeTiled", &fn, cudaEnableDefault, &qr);
    enc = (EncodeFn)fn;
    cudaFuncSetAttribute(k_mega, cudaFuncAttributeMaxDynamicSharedMemorySize, SM_TOTAL);
    cudaGetSymbolAddress(&p_spec, g_spec);
    cudaGetSymbolAddress(&p_wt, g_wt);
  }
  Maps m;
  const cuuint32_t es[3] = {1, 1, 1};
  {
    cuuint64_t dims[3] = {(cuuint64_t)D_, (cuuint64_t)S_, 1};
    cuuint64_t strides[2] = {(cuuint64_t)D_ * 2, (cuuint64_t)D_ * 2 * S_};
    cuuint32_t box[3] = {64, 128, 1};
    enc(&m.x, CU_TENSOR_MAP_DATA_TYPE_BFLOAT16, 3, (void*)x, dims, strides, box, es, CU_TENSOR_MAP_INTERLEAVE_NONE,
        CU_TENSOR_MAP_SWIZZLE_128B, CU_TENSOR_MAP_L2_PROMOTION_L2_128B, CU_TENSOR_MAP_FLOAT_OOB_FILL_NONE);
  }
  {
    cuuint64_t dims[3] = {32, 512, 56};
    cuuint64_t strides[2] = {(cuuint64_t)F_ * 2, 64};
    cuuint32_t box[3] = {32, 32, 7};
    enc(&m.w1, CU_TENSOR_MAP_DATA_TYPE_BFLOAT16, 3, (void*)w1, dims, strides, box, es, CU_TENSOR_MAP_INTERLEAVE_NONE,
        CU_TENSOR_MAP_SWIZZLE_64B, CU_TENSOR_MAP_L2_PROMOTION_L2_128B, CU_TENSOR_MAP_FLOAT_OOB_FILL_NONE);
  }
  {
    cuuint64_t dims[3] = {(cuuint64_t)D_, (cuuint64_t)F_, 1};
    cuuint64_t strides[2] = {(cuuint64_t)D_ * 2, (cuuint64_t)D_ * 2 * F_};
    cuuint32_t box[3] = {64, 112, 1};
    enc(&m.w2, CU_TENSOR_MAP_DATA_TYPE_BFLOAT16, 3, (void*)w2, dims, strides, box, es, CU_TENSOR_MAP_INTERLEAVE_NONE,
        CU_TENSOR_MAP_SWIZZLE_128B, CU_TENSOR_MAP_L2_PROMOTION_L2_128B, CU_TENSOR_MAP_FLOAT_OOB_FILL_NONE);
  }
  {
    cuuint64_t dims[2] = {(cuuint64_t)S_, 256};
    cuuint64_t strides[1] = {(cuuint64_t)S_ * 8};
    cuuint32_t box[2] = {16, 256};
    enc(&m.spec, CU_TENSOR_MAP_DATA_TYPE_FLOAT64, 2, p_spec, dims, strides, box, es, CU_TENSOR_MAP_INTERLEAVE_NONE,
        CU_TENSOR_MAP_SWIZZLE_128B, CU_TENSOR_MAP_L2_PROMOTION_NONE, CU_TENSOR_MAP_FLOAT_OOB_FILL_NONE);
  }
  {
    cuuint64_t dims[2] = {(cuuint64_t)S_, 257};
    cuuint64_t strides[1] = {(cuuint64_t)S_ * 4};
    cuuint32_t box[2] = {16, 32};
    enc(&m.wt, CU_TENSOR_MAP_DATA_TYPE_UINT32, 2, p_wt, dims, strides, box, es, CU_TENSOR_MAP_INTERLEAVE_NONE,
        CU_TENSOR_MAP_SWIZZLE_64B, CU_TENSOR_MAP_L2_PROMOTION_NONE, CU_TENSOR_MAP_FLOAT_OOB_FILL_NONE);
  }
  k_mega<<<129, NTHREADS, SM_TOTAL>>>(x, wr, wi, w1, b1, b2, out, m);
}
```

```cpp
#include <cuda_runtime.h>
#include <cuda_bf16.h>
#include <cuda.h>
#include <stdint.h>

namespace {

constexpr int S_ = 2048, D_ = 512, F_ = 1792, DF_ = 257;
constexpr int FC = 224;
constexpr int NJOB = 4;

__device__ __align__(1024) float2 g_spec[257 * 2048];
__device__ __align__(1024) uint32_t g_wt[257 * 2048];
__device__ uint4 g_part[16 * NJOB * 8 * 8 * 256];
__device__ float2 g_cs[8 * 32 * 112];
__device__ float2 g_stats[2048];
__device__ unsigned g_bar[2];
__device__ unsigned g_flag[16 * NJOB * 8];
#define TS(i)

__device__ __forceinline__ uint32_t smem_u32(const void* p) { return (uint32_t)__cvta_generic_to_shared(p); }
__device__ __forceinline__ float bf16r(float x) { return __bfloat162float(__float2bfloat16_rn(x)); }
__device__ __forceinline__ float bflo(uint32_t w) { return __uint_as_float(w << 16); }
__device__ __forceinline__ float bfhi(uint32_t w) { return __uint_as_float(w & 0xffff0000u); }
__device__ __forceinline__ uint32_t pack_bf16(float lo, float hi) {
  uint32_t r;
  asm("cvt.rn.bf16x2.f32 %0, %1, %2;" : "=r"(r) : "f"(hi), "f"(lo));
  return r;
}
__device__ __forceinline__ uint32_t hadd2_bf16(uint32_t a, uint32_t b) {
  uint32_t r;
  asm("add.rn.bf16x2 %0, %1, %2;" : "=r"(r) : "r"(a), "r"(b));
  return r;
}
__device__ __forceinline__ void named_bar(int id, int n) { asm volatile("bar.sync %0, %1;" ::"r"(id), "r"(n) : "memory"); }
__device__ __forceinline__ void fence_async() { asm volatile("fence.proxy.async;" ::: "memory"); }

__device__ __forceinline__ void mbar_init(uint32_t bar, int cnt) { asm volatile("mbarrier.init.shared::cta.b64 [%0], %1;" ::"r"(bar), "r"(cnt) : "memory"); }
__device__ __forceinline__ void mbar_expect_tx(uint32_t bar, uint32_t bytes) { asm volatile("mbarrier.arrive.expect_tx.shared::cta.b64 _, [%0], %1;" ::"r"(bar), "r"(bytes) : "memory"); }
__device__ __forceinline__ void mbar_arrive(uint32_t bar) { asm volatile("mbarrier.arrive.shared::cta.b64 _, [%0];" ::"r"(bar) : "memory"); }
__device__ __forceinline__ void mbar_wait(uint32_t bar, uint32_t parity) {
  asm volatile(
      "{\n.reg .pred p, q;\n.reg .u32 c;\nmov.u32 c, 0;\n"
      "MW_L%=:\nmbarrier.try_wait.parity.shared::cta.b64 p, [%0], %1, %2;\n@p bra MW_D%=;\n"
      "add.u32 c, c, 1;\nsetp.lt.u32 q, c, 131072;\n@q bra MW_L%=;\ntrap;\nMW_D%=:\n}\n"
      ::"r"(bar), "r"(parity), "r"(20000u) : "memory");
}
__device__ __forceinline__ void tma_load_3d(uint32_t dst, const CUtensorMap* map, int c0, int c1, int c2, uint32_t bar) {
  asm volatile("cp.async.bulk.tensor.3d.shared::cluster.global.mbarrier::complete_tx::bytes [%0], [%1, {%3, %4, %5}], [%2];"
               ::"r"(dst), "l"((uint64_t)map), "r"(bar), "r"(c0), "r"(c1), "r"(c2) : "memory");
}
__device__ __forceinline__ void tma_load_2d(uint32_t dst, const CUtensorMap* map, int c0, int c1, uint32_t bar) {
  asm volatile("cp.async.bulk.tensor.2d.shared::cluster.global.mbarrier::complete_tx::bytes [%0], [%1, {%3, %4}], [%2];"
               ::"r"(dst), "l"((uint64_t)map), "r"(bar), "r"(c0), "r"(c1) : "memory");
}
__device__ __forceinline__ void tma_store_2d(const CUtensorMap* map, int c0, int c1, uint32_t src) {
  asm volatile("cp.async.bulk.tensor.2d.global.shared::cta.bulk_group [%0, {%2, %3}], [%1];"
               ::"l"((uint64_t)map), "r"(src), "r"(c0), "r"(c1) : "memory");
}
__device__ __forceinline__ void tma_store_commit_wait() {
  asm volatile("cp.async.bulk.commit_group;" ::: "memory");
  asm volatile("cp.async.bulk.wait_group 0;" ::: "memory");
}
__device__ __forceinline__ void wgmma_fence() { asm volatile("wgmma.fence.sync.aligned;" ::: "memory"); }
__device__ __forceinline__ void wgmma_commit() { asm volatile("wgmma.commit_group.sync.aligned;" ::: "memory"); }
template <int N> __device__ __forceinline__ void wgmma_wait() { asm volatile("wgmma.wait_group.sync.aligned %0;" ::"n"(N) : "memory"); }
__device__ __forceinline__ uint64_t make_desc(uint32_t addr, uint32_t lbo_bytes, uint32_t sbo_bytes, uint32_t swz) {
  uint64_t d = 0;
  d |= (uint64_t)((addr & 0x3FFFF) >> 4);
  d |= (uint64_t)((lbo_bytes & 0x3FFFF) >> 4) << 16;
  d |= (uint64_t)((sbo_bytes & 0x3FFFF) >> 4) << 32;
  d |= (uint64_t)swz << 62;
  return d;
}
__device__ __forceinline__ unsigned ld_acquire(const unsigned* p) {
  unsigned v;
  asm volatile("ld.acquire.gpu.global.u32 %0, [%1];" : "=r"(v) : "l"(p) : "memory");
  return v;
}

__device__ __forceinline__ void wgmma_n224_ss(float (&d)[112], uint64_t da, uint64_t db, int scale_d) {
  asm volatile("{\n.reg .pred p;\nsetp.ne.b32 p, %114, 0;\n"
    "wgmma.mma_async.sync.aligned.m64n224k16.f32.bf16.bf16 {%0, %1, %2, %3, %4, %5, %6, %7, %8, %9, %10, %11, %12, %13, %14, %15, %16, %17, %18, %19, %20, %21, %22, %23, %24, %25, %26, %27, %28, %29, %30, %31, %32, %33, %34, %35, %36, %37, %38, %39, %40, %41, %42, %43, %44, %45, %46, %47, %48, %49, %50, %51, %52, %53, %54, %55, %56, %57, %58, %59, %60, %61, %62, %63, %64, %65, %66, %67, %68, %69, %70, %71, %72, %73, %74, %75, %76, %77, %78, %79, %80, %81, %82, %83, %84, %85, %86, %87, %88, %89, %90, %91, %92, %93, %94, %95, %96, %97, %98, %99, %100, %101, %102, %103, %104, %105, %106, %107, %108, %109, %110, %111}, %112, %113, p, 1, 1, 0, 1;\n}\n"
    : "+f"(d[0]), "+f"(d[1]), "+f"(d[2]), "+f"(d[3]), "+f"(d[4]), "+f"(d[5]), "+f"(d[6]), "+f"(d[7]), "+f"(d[8]), "+f"(d[9]), "+f"(d[10]), "+f"(d[11]), "+f"(d[12]), "+f"(d[13]), "+f"(d[14]), "+f"(d[15]), "+f"(d[16]), "+f"(d[17]), "+f"(d[18]), "+f"(d[19]), "+f"(d[20]), "+f"(d[21]), "+f"(d[22]), "+f"(d[23]), "+f"(d[24]), "+f"(d[25]), "+f"(d[26]), "+f"(d[27]), "+f"(d[28]), "+f"(d[29]), "+f"(d[30]), "+f"(d[31]), "+f"(d[32]), "+f"(d[33]), "+f"(d[34]), "+f"(d[35]), "+f"(d[36]), "+f"(d[37]), "+f"(d[38]), "+f"(d[39]), "+f"(d[40]), "+f"(d[41]), "+f"(d[42]), "+f"(d[43]), "+f"(d[44]), "+f"(d[45]), "+f"(d[46]), "+f"(d[47]), "+f"(d[48]), "+f"(d[49]), "+f"(d[50]), "+f"(d[51]), "+f"(d[52]), "+f"(d[53]), "+f"(d[54]), "+f"(d[55]), "+f"(d[56]), "+f"(d[57]), "+f"(d[58]), "+f"(d[59]), "+f"(d[60]), "+f"(d[61]), "+f"(d[62]), "+f"(d[63]), "+f"(d[64]), "+f"(d[65]), "+f"(d[66]), "+f"(d[67]), "+f"(d[68]), "+f"(d[69]), "+f"(d[70]), "+f"(d[71]), "+f"(d[72]), "+f"(d[73]), "+f"(d[74]), "+f"(d[75]), "+f"(d[76]), "+f"(d[77]), "+f"(d[78]), "+f"(d[79]), "+f"(d[80]), "+f"(d[81]), "+f"(d[82]), "+f"(d[83]), "+f"(d[84]), "+f"(d[85]), "+f"(d[86]), "+f"(d[87]), "+f"(d[88]), "+f"(d[89]), "+f"(d[90]), "+f"(d[91]), "+f"(d[92]), "+f"(d[93]), "+f"(d[94]), "+f"(d[95]), "+f"(d[96]), "+f"(d[97]), "+f"(d[98]), "+f"(d[99]), "+f"(d[100]), "+f"(d[101]), "+f"(d[102]), "+f"(d[103]), "+f"(d[104]), "+f"(d[105]), "+f"(d[106]), "+f"(d[107]), "+f"(d[108]), "+f"(d[109]), "+f"(d[110]), "+f"(d[111])
    : "l"(da), "l"(db), "r"(scale_d));
}
__device__ __forceinline__ void wgmma_n128_rs(float (&d)[64], uint32_t a0, uint32_t a1, uint32_t a2, uint32_t a3, uint64_t db, int scale_d) {
  asm volatile("{\n.reg .pred p;\nsetp.ne.b32 p, %69, 0;\n"
    "wgmma.mma_async.sync.aligned.m64n128k16.f32.bf16.bf16 {%0, %1, %2, %3, %4, %5, %6, %7, %8, %9, %10, %11, %12, %13, %14, %15, %16, %17, %18, %19, %20, %21, %22, %23, %24, %25, %26, %27, %28, %29, %30, %31, %32, %33, %34, %35, %36, %37, %38, %39, %40, %41, %42, %43, %44, %45, %46, %47, %48, %49, %50, %51, %52, %53, %54, %55, %56, %57, %58, %59, %60, %61, %62, %63}, {%64, %65, %66, %67}, %68, p, 1, 1, 1;\n}\n"
    : "+f"(d[0]), "+f"(d[1]), "+f"(d[2]), "+f"(d[3]), "+f"(d[4]), "+f"(d[5]), "+f"(d[6]), "+f"(d[7]), "+f"(d[8]), "+f"(d[9]), "+f"(d[10]), "+f"(d[11]), "+f"(d[12]), "+f"(d[13]), "+f"(d[14]), "+f"(d[15]), "+f"(d[16]), "+f"(d[17]), "+f"(d[18]), "+f"(d[19]), "+f"(d[20]), "+f"(d[21]), "+f"(d[22]), "+f"(d[23]), "+f"(d[24]), "+f"(d[25]), "+f"(d[26]), "+f"(d[27]), "+f"(d[28]), "+f"(d[29]), "+f"(d[30]), "+f"(d[31]), "+f"(d[32]), "+f"(d[33]), "+f"(d[34]), "+f"(d[35]), "+f"(d[36]), "+f"(d[37]), "+f"(d[38]), "+f"(d[39]), "+f"(d[40]), "+f"(d[41]), "+f"(d[42]), "+f"(d[43]), "+f"(d[44]), "+f"(d[45]), "+f"(d[46]), "+f"(d[47]), "+f"(d[48]), "+f"(d[49]), "+f"(d[50]), "+f"(d[51]), "+f"(d[52]), "+f"(d[53]), "+f"(d[54]), "+f"(d[55]), "+f"(d[56]), "+f"(d[57]), "+f"(d[58]), "+f"(d[59]), "+f"(d[60]), "+f"(d[61]), "+f"(d[62]), "+f"(d[63])
    : "r"(a0), "r"(a1), "r"(a2), "r"(a3), "l"(db), "r"(scale_d));
}

__device__ __forceinline__ float2 cadd(float2 a, float2 b) { return make_float2(a.x + b.x, a.y + b.y); }
__device__ __forceinline__ float2 csub(float2 a, float2 b) { return make_float2(a.x - b.x, a.y - b.y); }
__device__ __forceinline__ float2 cmul(float2 a, float2 b) { return make_float2(a.x * b.x - a.y * b.y, a.x * b.y + a.y * b.x); }
__device__ __forceinline__ float2 cconj(float2 a) { return make_float2(a.x, -a.y); }

template <int DIR> __device__ __forceinline__ void dft4(float2& a0, float2& a1, float2& a2, float2& a3) {
  float2 t0 = cadd(a0, a2), t1 = csub(a0, a2), t2 = cadd(a1, a3), t3 = csub(a1, a3);
  float2 t3r = DIR < 0 ? make_float2(t3.y, -t3.x) : make_float2(-t3.y, t3.x);
  a0 = cadd(t0, t2); a2 = csub(t0, t2); a1 = cadd(t1, t3r); a3 = csub(t1, t3r);
}
template <int DIR> __device__ __forceinline__ float2 mulw(float2 v, float c, float s) {
  return DIR < 0 ? make_float2(v.x * c + v.y * s, v.y * c - v.x * s) : make_float2(v.x * c - v.y * s, v.y * c + v.x * s);
}
template <int DIR> __device__ __forceinline__ float2 muli(float2 v) {
  return DIR < 0 ? make_float2(v.y, -v.x) : make_float2(-v.y, v.x);
}
#define O16(k) (4 * ((k) & 3) + ((k) >> 2))
#define O8(k) (2 * ((k) & 3) + ((k) >> 2))
template <int DIR> __device__ __forceinline__ void dft16(float2 (&v)[16]) {
  constexpr float C1 = 0.92387953251128674f, S1 = 0.38268343236508977f, R = 0.70710678118654752f;
#pragma unroll
  for (int n2 = 0; n2 < 4; n2++) dft4<DIR>(v[n2], v[4 + n2], v[8 + n2], v[12 + n2]);
  v[5] = mulw<DIR>(v[5], C1, S1);
  v[6] = mulw<DIR>(v[6], R, R);
  v[7] = mulw<DIR>(v[7], S1, C1);
  v[9] = mulw<DIR>(v[9], R, R);
  v[10] = muli<DIR>(v[10]);
  v[11] = mulw<DIR>(v[11], -R, R);
  v[13] = mulw<DIR>(v[13], S1, C1);
  v[14] = mulw<DIR>(v[14], -R, R);
  v[15] = mulw<DIR>(v[15], -C1, -S1);
#pragma unroll
  for (int k1 = 0; k1 < 4; k1++) dft4<DIR>(v[4 * k1], v[4 * k1 + 1], v[4 * k1 + 2], v[4 * k1 + 3]);
}
template <int DIR> __device__ __forceinline__ void dft8(float2 (&v)[8]) {
  constexpr float R = 0.70710678118654752f;
  dft4<DIR>(v[0], v[2], v[4], v[6]);
  dft4<DIR>(v[1], v[3], v[5], v[7]);
  v[3] = mulw<DIR>(v[3], R, R);
  v[5] = muli<DIR>(v[5]);
  v[7] = mulw<DIR>(v[7], -R, R);
#pragma unroll
  for (int k1 = 0; k1 < 4; k1++) {
    float2 a = v[2 * k1], b = v[2 * k1 + 1];
    v[2 * k1] = cadd(a, b); v[2 * k1 + 1] = csub(a, b);
  }
}
template <int N> __device__ __forceinline__ float2 twcs(int m) {
  m &= (N - 1);
  if (m >= N / 2) m -= N;
  float s, c;
  __sincosf((float)m * (6.283185307179586f / N), &s, &c);
  return make_float2(c, s);
}

__device__ __forceinline__ void twiddle16(float2 (&v)[16], int m) {
  const float2 w1 = twcs<2048>(m);
  float2 w = w1;
#pragma unroll
  for (int k = 1; k < 16; k++) {
    v[O16(k)] = mulw<-1>(v[O16(k)], w.x, w.y);
    if (k < 15) w = cmul(w, w1);
  }
}
__device__ __forceinline__ float2* tile_at(uint8_t* tile, int k, int r) {
  return reinterpret_cast<float2*>(tile + k * 128 + ((((r >> 1) ^ k) & 7) << 4) + (r & 1) * 8);
}
constexpr int SPITCH = 260;

constexpr int STEP = 45056;
constexpr int W1_STAGE = 14336;
constexpr int SM_FFT = 184 * 1024;
constexpr int SM_WT = SM_FFT + 32768;
constexpr int SM_BAR = SM_WT + 8192;
constexpr int SM_TAB = SM_BAR + 256;
constexpr int SM_TOTAL = SM_TAB + 1280;
constexpr int NTHREADS = 384;

__device__ __forceinline__ float gelu2(float x) {
  float u = x * (0.7978845608028654f + 0.035677408136300125f * x * x);
  float th;
  asm("tanh.approx.f32 %0, %1;" : "=f"(th) : "f"(u));
  return fmaf(x, th, x);
}
__device__ __forceinline__ unsigned grid_arrive(unsigned* cnt) {
  __threadfence();
  unsigned old = atomicAdd(cnt, 1u);
  return (old / 129u + 1u) * 129u;
}
__device__ __forceinline__ void grid_wait(const unsigned* cnt, unsigned target) {
  int it = 0;
  while ((int)(ld_acquire(cnt) - target) < 0) {
    if (++it > (1 << 22)) __trap();
  }
}
__device__ __forceinline__ uint32_t piece_off(int p) {
  if (p >= 12) p -= 12;
  const int s = (p * 11) >> 5;
  return (uint32_t)(s * STEP + (p - 3 * s) * W1_STAGE);
}

struct Maps { CUtensorMap x, w1, w2, spec, wt; };

__device__ __forceinline__ void issue_items(const uint8_t* smem, int first, int n) {
#pragma unroll 1
  for (int i = first; i < first + n; i++) {
    const uint4 a = *reinterpret_cast<const uint4*>(smem + SM_TAB + i * 32);
    const uint4 c = *reinterpret_cast<const uint4*>(smem + SM_TAB + i * 32 + 16);
    if (c.w) mbar_expect_tx(a.w, c.w);
    tma_load_3d(a.z, reinterpret_cast<const CUtensorMap*>((uint64_t)a.x | ((uint64_t)a.y << 32)), (int)c.x, (int)c.y, (int)c.z, a.w);
  }
}

__device__ __forceinline__ void gemm_part(uint8_t* smem, const Maps& maps, const __nv_bfloat16* __restrict__ b1, int rt, int sp) {
  const uint32_t sb = smem_u32(smem);
  const int tid = threadIdx.x, warp = tid >> 5, lane = tid & 31, wg = warp >> 2;
  const uint32_t bar_full1 = sb + SM_BAR, bar_full2 = sb + SM_BAR + 64;
  unsigned* relcnt = reinterpret_cast<unsigned*>(smem + SM_BAR + 128);
  const uint32_t bar_stats = sb + SM_BAR + 160, bar_st = sb + SM_BAR + 224;
  uint32_t ha[56];
      auto release = [&](int j) {
        __syncwarp();
        if (lane == 0) {
          __threadfence_block();
          if ((atomicAdd(&relcnt[j & 3], 1u) & 7u) == 7u) {
            __threadfence_block();
            issue_items(smem, 3 * j + 12, 3);
          }
        }
      };
      {
        float acc[112];
#pragma unroll
        for (int i = 0; i < 112; i++) acc[i] = 0.f;
        const uint64_t dA = make_desc(sb + __shfl_sync(0xffffffffu, wg, 0) * 8192, 16, 1024, 1), dB = make_desc(sb + 16384, 2048, 512, 2);
#pragma unroll 1
        for (int j = 0; j < 8; j++) {
          const uint32_t base = (j & 3) * STEP;
          mbar_wait(bar_full1 + 8 * (j & 3), j >> 2);
          if (tid == 0) TS(24 + j);
          wgmma_fence();
#pragma unroll
          for (int kk = 0; kk < 4; kk++)
            wgmma_n224_ss(acc, dA + ((base + kk * 32) >> 4), dB + ((base + (kk >> 1) * W1_STAGE + (kk & 1) * 1024) >> 4), 1);
          wgmma_commit();
          if (j > 0) {
            wgmma_wait<1>();
            release(j - 1);
          }
        }
        mbar_wait(bar_stats, 0);
        if (tid < 224) {
          float c0 = 0.f, c1 = 0.f;
          const float2* pc = g_cs + (sp * 32 + (tid & 1) * 16) * 112 + (tid >> 1);
#pragma unroll
          for (int i = 0; i < 16; i++) { const float2 c = __ldcg(pc + i * 112); c0 += c.x; c1 += c.y; }
          c0 += __shfl_xor_sync(0xffffffffu, c0, 1); c1 += __shfl_xor_sync(0xffffffffu, c1, 1);
          const uint32_t bw = __ldg(reinterpret_cast<const uint32_t*>(b1 + sp * FC) + (tid >> 1));
          reinterpret_cast<float4*>(smem + SM_WT)[tid >> 1] = make_float4(c0, c1, bflo(bw), bfhi(bw));
        }
        const int row = rt * 128 + warp * 16 + (lane >> 2);
        const float2 st0 = __ldcg(&g_stats[row]), st1 = __ldcg(&g_stats[row + 8]);
        wgmma_wait<0>();
        if (tid == 0) TS(2);
        named_bar(1, 256);
        if (tid == 0) {
          issue_items(smem, 33, 3);
        }
        if (tid == 0) TS(3);
        const float4* csb = reinterpret_cast<const float4*>(smem + SM_WT) + (lane & 3);
#pragma unroll
        for (int j = 0; j < 28; j++) {
          const float4 c = csb[j * 4];
          ha[2 * j] = pack_bf16(gelu2(fmaf(fmaf(-st0.x, c.x, acc[4 * j]), st0.y, c.z)), gelu2(fmaf(fmaf(-st0.x, c.y, acc[4 * j + 1]), st0.y, c.w)));
          ha[2 * j + 1] = pack_bf16(gelu2(fmaf(fmaf(-st1.x, c.x, acc[4 * j + 2]), st1.y, c.z)), gelu2(fmaf(fmaf(-st1.x, c.y, acc[4 * j + 3]), st1.y, c.w)));
        }
      }
      if (tid == 0) TS(4);
      if (wg == 1) named_bar(2, 256);
#pragma unroll 1
      for (int jq = 0; jq < NJOB; jq++) {
        float acc[64];
#pragma unroll
        for (int h = 0; h < 2; h++) {
          const uint32_t o0 = piece_off(4 * jq + 2 * h), o1 = piece_off(4 * jq + 2 * h + 1);
          const uint64_t dW = make_desc(sb + o0, o1 - o0, 1024, 1);
          mbar_wait(bar_full2 + 8 * (2 * jq + h), 0);
          wgmma_fence();
#pragma unroll
          for (int kk = 0; kk < 7; kk++) {
            const int kb = h * 7 + kk;
            wgmma_n128_rs(acc, ha[4 * kb], ha[4 * kb + 1], ha[4 * kb + 2], ha[4 * kb + 3], dW + kk * 128, kb > 0);
          }
          wgmma_commit();
        }
        if (jq == 0 && wg == 0) asm volatile("bar.arrive 2, 256;" ::: "memory");
        wgmma_wait<0>();
        if (jq == 0 && lane == 0) {
          __threadfence_block();
          if (atomicAdd(&relcnt[4], 1u) == 7u) {
            __threadfence_block();
            issue_items(smem, 36, 4);
          }
        }
        uint4* dstp = g_part + ((((size_t)rt * NJOB + jq) * 8 + warp) * 8 + sp) * 256 + lane;
#pragma unroll
        for (int i = 0; i < 8; i++)
          dstp[i * 32] = make_uint4(pack_bf16(acc[8 * i], acc[8 * i + 1]), pack_bf16(acc[8 * i + 2], acc[8 * i + 3]),
                                    pack_bf16(acc[8 * i + 4], acc[8 * i + 5]), pack_bf16(acc[8 * i + 6], acc[8 * i + 7]));
        __syncwarp();
        if (lane == 0) mbar_arrive(bar_st + 8 * jq);
        if (tid == 0) TS(5 + jq);
      }
}

__global__ void __launch_bounds__(NTHREADS, 1)
k_mega(const __nv_bfloat16* __restrict__ x, const __nv_bfloat16* __restrict__ wr, const __nv_bfloat16* __restrict__ wi,
       const __nv_bfloat16* __restrict__ w1, const __nv_bfloat16* __restrict__ b1, const __nv_bfloat16* __restrict__ b2, __nv_bfloat16* __restrict__ out,
       const __grid_constant__ Maps maps) {
  extern __shared__ __align__(1024) uint8_t smem[];
  const uint32_t sb = smem_u32(smem);
  const int rt = blockIdx.x >> 3, sp = blockIdx.x & 7;
  const int warp = threadIdx.x >> 5, lane = threadIdx.x & 31;
  const int s0 = blockIdx.x * 16;
  if (threadIdx.x == 0) TS(0);
  const uint32_t bar_full1 = sb + SM_BAR;
  const uint32_t bar_full2 = sb + SM_BAR + 64;
  unsigned* relcnt = reinterpret_cast<unsigned*>(smem + SM_BAR + 128);
  const uint32_t bar_stats = sb + SM_BAR + 160;
  const uint32_t bar_p1 = sb + SM_BAR + 168;
  const uint32_t bar_tile = sb + SM_BAR + 176;
  const uint32_t bar_st = sb + SM_BAR + 224;
  const uint32_t bar_g = sb + SM_BAR + 192;
  uint8_t* tile = smem + SM_FFT;

  if (threadIdx.x == 0) {
    for (int i = 0; i < 4; i++) mbar_init(bar_full1 + 8 * i, 1);
    for (int i = 0; i < 8; i++) mbar_init(bar_full2 + 8 * i, 2);
    mbar_init(bar_stats, 1); mbar_init(bar_p1, 256); mbar_init(bar_tile, 1);
    for (int i = 0; i < 4; i++) { mbar_init(bar_g + 8 * i, 1); mbar_init(bar_st + 8 * i, 8); }
    for (int i = 0; i < 5; i++) relcnt[i] = 0;
    asm volatile("fence.mbarrier_init.release.cluster;" ::: "memory");
  }
  if (warp == 1) {
#pragma unroll 1
    for (int i = lane; i < 40; i += 32) {
      uint64_t mp; uint32_t dst, bar, bytes; int c0, c1, c2;
      if (i < 24) {
        const int j = (i * 11) >> 5, part = i - 3 * j;
        bar = bar_full1 + 8 * (j & 3);
        bytes = part ? 0 : STEP;
        dst = sb + (j & 3) * STEP + (part ? 16384 + (part - 1) * W1_STAGE : 0);
        mp = (uint64_t)(part ? &maps.w1 : &maps.x);
        c0 = part ? 0 : j * 64; c1 = part ? j * 64 + (part - 1) * 32 : rt * 128; c2 = part ? sp * 7 : 0;
      } else {
        const int p = i - 24;
        bar = bar_full2 + 8 * (p >> 1);
        bytes = W1_STAGE;
        dst = sb + piece_off(p);
        mp = (uint64_t)&maps.w2;
        c0 = (p >> 2) * 128 + (p & 1) * 64; c1 = sp * FC + ((p >> 1) & 1) * 112; c2 = 0;
      }
      *reinterpret_cast<uint4*>(smem + SM_TAB + i * 32) = make_uint4((uint32_t)mp, (uint32_t)(mp >> 32), dst, bar);
      *reinterpret_cast<uint4*>(smem + SM_TAB + i * 32 + 16) = make_uint4(c0, c1, c2, bytes);
    }
  }
  __syncthreads();
  if (threadIdx.x == 32 && blockIdx.x < 128) issue_items(smem, 0, 12);

  if (warp >= 8) {
    const int t = threadIdx.x & 127;
    const bool extra = blockIdx.x == 128;
    if (!extra) {
      const uint32_t stg = (uint32_t)(SM_WT + (warp - 8) * 2048);
      if (t < 16) {
        const size_t o = (size_t)(s0 + t) * DF_ + 256;
        g_wt[(size_t)256 * S_ + s0 + t] = (uint32_t)__ldg(reinterpret_cast<const unsigned short*>(wr) + o) |
                                          ((uint32_t)__ldg(reinterpret_cast<const unsigned short*>(wi) + o) << 16);
      }
      uint32_t wv[2][16];
      {
        const unsigned short* pr = reinterpret_cast<const unsigned short*>(wr) + (size_t)s0 * DF_ + t;
        const unsigned short* pi = reinterpret_cast<const unsigned short*>(wi) + (size_t)s0 * DF_ + t;
#pragma unroll
        for (int u = 0; u < 32; u++)
          wv[u >> 4][u & 15] = (uint32_t)__ldg(pr + (u & 15) * DF_ + (u >> 4) * 128) | ((uint32_t)__ldg(pi + (u & 15) * DF_ + (u >> 4) * 128) << 16);
      }
#pragma unroll
      for (int rd = 0; rd < 2; rd++) {
        if (rd && lane == 0) asm volatile("cp.async.bulk.wait_group.read 0;" ::: "memory");
        __syncwarp();
#pragma unroll
        for (int c = 0; c < 4; c++)
          *reinterpret_cast<uint4*>(smem + stg + lane * 64 + ((c ^ ((lane >> 1) & 3)) << 4)) =
              make_uint4(wv[rd][4 * c], wv[rd][4 * c + 1], wv[rd][4 * c + 2], wv[rd][4 * c + 3]);
        fence_async();
        __syncwarp();
        if (lane == 0) {
          tma_store_2d(&maps.wt, s0, rd * 128 + (warp - 8) * 32, sb + stg);
          asm volatile("cp.async.bulk.commit_group;" ::: "memory");
        }
      }
      if (lane == 0) { asm volatile("cp.async.bulk.wait_group 0;" ::: "memory"); __threadfence(); }
    }
    named_bar(3, 128);
    if (t == 0) {
      TS(11);
      if (!extra) {
        mbar_wait(bar_p1, 0);
        tma_store_2d(&maps.spec, s0, 0, sb + SM_FFT);
        tma_store_commit_wait();
      }
      TS(12);
      const unsigned target = grid_arrive(&g_bar[0]);
      grid_wait(&g_bar[0], target);
      mbar_arrive(bar_stats);
    }
    named_bar(3, 128);
    if (t == 0) TS(13);
    {
      float2* buf = reinterpret_cast<float2*>(tile);
      const int k1 = t >> 3, m2 = t & 7;
      const int c0 = extra ? 256 : blockIdx.x * 2, nc = extra ? 1 : 2;
      float2 vn[16];
      uint32_t wn[16];
#pragma unroll 1
      for (int c = -1; c < nc; c++) {
        uint32_t wq[16];
        if (c >= 0) {
#pragma unroll
          for (int i = 0; i < 16; i++) { buf[128 * i + t] = vn[i]; wq[i] = wn[i]; }
        }
        if (c + 1 < nc) {
#pragma unroll
          for (int i = 0; i < 16; i++) {
            vn[i] = __ldcg(g_spec + (size_t)(c0 + c + 1) * S_ + 128 * i + t);
            wn[i] = __ldcg(g_wt + (size_t)(c0 + c + 1) * S_ + 128 * i + t);
          }
        }
        if (c < 0) continue;
#pragma unroll 1
        for (int it = 0; it < 2; it++) {
#pragma unroll 1
          for (int p = 0; p < 2; p++) {
            const float2* in = buf + (p ? k1 * 136 + m2 : t);
            const int is = p ? 8 : 128;
            float2 v[16];
#pragma unroll
            for (int i = 0; i < 16; i++) v[i] = in[i * is];
            dft16<-1>(v);
            twiddle16(v, p ? 16 * m2 : t);
            named_bar(3, 128);
            float2* o = buf + (p ? k1 * 9 + m2 : t);
            const int os = p ? 144 : 136;
#pragma unroll
            for (int kk = 0; kk < 16; kk++) o[kk * os] = v[O16(kk)];
            named_bar(3, 128);
          }
          float2 e[2][8];
#pragma unroll
          for (int m = 0; m < 8; m++) { e[0][m] = buf[t * 9 + m]; e[1][m] = buf[(t + 128) * 9 + m]; }
          dft8<-1>(e[0]);
          dft8<-1>(e[1]);
          named_bar(3, 128);
          if (it == 0) {
            constexpr float SC = 1.0f / (2048.0f * 512.0f);
#pragma unroll
            for (int i = 0; i < 16; i++)
              buf[128 * i + t] = cconj(cmul(e[i & 1][O8(i >> 1)], make_float2(bflo(wq[i]) * SC, bfhi(wq[i]) * SC)));
          } else {
            float2* col = g_spec + (size_t)(c0 + c) * S_ + t;
#pragma unroll
            for (int i = 0; i < 16; i++) col[128 * i] = cconj(e[i & 1][O8(i >> 1)]);
          }
        }
      }
    }
    named_bar(3, 128);
    if (warp == 9 && lane < 8 && !extra) {
#pragma unroll 1
      for (int jq = 0; jq < NJOB; jq++) {
        mbar_wait(bar_st + 8 * jq, 0);
        __threadfence();
        atomicAdd(&g_flag[(rt * NJOB + jq) * 8 + lane], 1u);
      }
    }
    if (t == 64 && !extra) {
        mbar_wait(bar_st + 24, 0);
#pragma unroll 1
        for (int jq = 0; jq < NJOB; jq++) {
          unsigned* fl = &g_flag[(rt * NJOB + jq) * 8 + sp];
          int it = 0;
          while (ld_acquire(fl) < 8u) {
            if (++it > (1 << 22)) __trap();
          }
          *fl = 0u;
          fence_async();
          mbar_expect_tx(bar_g + 8 * jq, jq ? 32768 : 32768 + 17 * 1024);
          asm volatile("cp.async.bulk.shared::cluster.global.mbarrier::complete_tx::bytes [%0], [%1], %2, [%3];"
                       ::"r"(sb + jq * 32768), "l"(g_part + (((size_t)rt * NJOB + jq) * 8 + sp) * 8 * 256), "r"(32768), "r"(bar_g + 8 * jq) : "memory");
          if (jq == 0) {
#pragma unroll 1
            for (int i = 0; i < 17; i++)
              asm volatile("cp.async.bulk.shared::cluster.global.mbarrier::complete_tx::bytes [%0], [%1], %2, [%3];"
                           ::"r"(sb + 131072 + i * SPITCH * 4), "l"(i < 16 ? x + (size_t)(s0 + i) * D_ : b2), "r"(1024), "r"(bar_g) : "memory");
          }
        }
    }
    if (t == 0) {
      TS(14);
      const unsigned target = grid_arrive(&g_bar[1]);
      if (!extra) {
        grid_wait(&g_bar[1], target);
        TS(15);
        fence_async();
        mbar_expect_tx(bar_tile, 32768);
        tma_load_2d(sb + SM_FFT, &maps.spec, s0, 0, bar_tile);
      }
    }
  } else {
    if (blockIdx.x == 128) return;
    const int tid = threadIdx.x;
    const int r = tid & 15, q = tid >> 4;
#pragma unroll 1
    for (int ph = 0; ph < 3; ph++) {
      if (ph) {
        float y256 = 0.f;
        if (ph == 2) {
          mbar_wait(bar_tile, 0);
          if (tid == 0) TS(17);
          y256 = __ldcg(&g_spec[(size_t)256 * S_ + s0 + r]).x;
        }
        const float sg = ph == 1 ? -1.f : 1.f, sc = ph == 1 ? 0.5f : 1.f;
        float2 tw = twcs<512>(q);
#pragma unroll 2
        for (int i = 0; i < 8; i++) {
          const int j = q + 16 * i;
          float2* pa = tile_at(tile, j, r);
          float2* pb = tile_at(tile, j == 0 ? 128 : 256 - j, r);
          const float2 A = *pa, B = *pb;
          const float2 P = make_float2(sc * (A.x + B.x), sc * (A.y - B.y)), M = make_float2(sc * (A.x - B.x), sc * (A.y + B.y));
          const float ts = sg * tw.y;
          const float2 T = make_float2(M.x * tw.x - M.y * ts, M.y * tw.x + M.x * ts);
          tw = cmul(tw, make_float2(0.98078528040323044f, 0.19509032201612825f));
          const float2 V = make_float2(-sg * T.y, sg * T.x);
          if (j) {
            *pa = make_float2(P.x + V.x, -sg * (P.y + V.y));
            *pb = make_float2(P.x - V.x, sg * (P.y - V.y));
          } else if (ph == 1) {
            g_spec[(size_t)256 * S_ + s0 + r] = make_float2(A.x - A.y, 0.f);
            *pa = make_float2(A.x + A.y, 0.f);
            *pb = cconj(B);
          } else {
            *pa = make_float2(A.x + y256, y256 - A.x);
            *pb = make_float2(2.f * B.x, 2.f * B.y);
          }
        }
      }
      if (ph == 1) {
        fence_async();
        mbar_arrive(bar_p1);
        gemm_part(smem, maps, b1, rt, sp);
        continue;
      }
      if (ph == 0) {
        uint32_t w[16];
        const uint32_t* xw = reinterpret_cast<const uint32_t*>(x + (size_t)(s0 + q) * D_);
#pragma unroll
        for (int n1 = 0; n1 < 16; n1++) w[n1] = __ldg(xw + 16 * n1 + r);
        if ((tid & 127) < 112) {
          const uint32_t* pw = reinterpret_cast<const uint32_t*>(w1 + (size_t)(rt * 32 + (tid >> 7) * 16) * F_ + sp * FC) + (tid & 127);
          float c0 = 0.f, c1 = 0.f;
#pragma unroll
          for (int k = 0; k < 16; k++) { const uint32_t ww = __ldg(pw + k * (F_ / 2)); c0 += bflo(ww); c1 += bfhi(ww); }
          g_cs[(sp * 32 + rt * 2 + (tid >> 7)) * 112 + (tid & 127)] = make_float2(c0, c1);
        }
        float sum = 0.f;
#pragma unroll
        for (int n1 = 0; n1 < 16; n1++) sum += bflo(w[n1]) + bfhi(w[n1]);
#pragma unroll
        for (int o = 1; o < 16; o <<= 1) sum += __shfl_xor_sync(0xffffffffu, sum, o);
        const float mean = sum * (1.0f / D_);
        float sq = 0.f;
#pragma unroll
        for (int n1 = 0; n1 < 16; n1++) {
          float a = bflo(w[n1]) - mean, c = bfhi(w[n1]) - mean;
          sq += a * a + c * c;
        }
#pragma unroll
        for (int o = 1; o < 16; o <<= 1) sq += __shfl_xor_sync(0xffffffffu, sq, o);
        const uint32_t nm2 = pack_bf16(-mean, -mean);
        float sd, rs;
        asm("sqrt.approx.f32 %0, %1;" : "=f"(sd) : "f"(bf16r(bf16r(sq * (1.0f / D_)) + 1e-5f)));
        asm("rcp.approx.f32 %0, %1;" : "=f"(rs) : "f"(bf16r(sd)));
        if (r == 0) g_stats[s0 + q] = make_float2(-bflo(nm2), rs);
#pragma unroll
        for (int n1 = 0; n1 < 16; n1++) {
          const uint32_t d = hadd2_bf16(w[n1], nm2);
          const uint32_t xn = pack_bf16(bflo(d) * rs, bfhi(d) * rs);
          *tile_at(tile, 16 * n1 + r, q) = make_float2(bflo(xn), bfhi(xn));
        }
      }
      named_bar(1, 256);
      {
        uint8_t* pa = reinterpret_cast<uint8_t*>(tile_at(tile, q, r));
        const uint8_t* pb = tile + q * 2048 + (r & 1) * 8;
#pragma unroll 1
        for (int p = 0; p < 2; p++) {
          float2 v[16];
#pragma unroll
          for (int i = 0; i < 16; i++)
            v[i] = *reinterpret_cast<const float2*>(p ? pb + i * 128 + ((((r >> 1) ^ i) & 7) << 4) : pa + i * 2048);
          dft16<-1>(v);
          if (p == 0) twiddle16(v, 8 * q);
          named_bar(1, 256);
          if (p && ph) {
#pragma unroll
            for (int i = 0; i < 16; i++) reinterpret_cast<uint32_t*>(tile)[r * SPITCH + q + 16 * i] = pack_bf16(v[O16(i)].x, -v[O16(i)].y);
          } else {
#pragma unroll
            for (int i = 0; i < 16; i++) *reinterpret_cast<float2*>(pa + i * 2048) = v[O16(i)];
          }
          named_bar(1, 256);
        }
      }
      if (tid == 0 && ph == 0) TS(10);
    }
    if (tid == 0) TS(16);
    {
      const int g = lane >> 2;
      const uint32_t* stile = reinterpret_cast<const uint32_t*>(tile);
      const uint32_t* xs = reinterpret_cast<const uint32_t*>(smem + 131072);
#pragma unroll 1
      for (int jq = 0; jq < NJOB; jq++) {
        const int cw = jq * 64 + 8 * warp + (lane & 3);
        mbar_wait(bar_g + 8 * jq, 0);
        const uint4* src = reinterpret_cast<const uint4*>(smem + jq * 32768) + tid;
        float o[8];
#pragma unroll
        for (int c = 0; c < 8; c++) o[c] = 0.f;
#pragma unroll
        for (int s = 0; s < 8; s++) {
          const uint4 v = src[s * 256];
          o[0] += bflo(v.x); o[1] += bfhi(v.x); o[2] += bflo(v.y); o[3] += bfhi(v.y);
          o[4] += bflo(v.z); o[5] += bfhi(v.z); o[6] += bflo(v.w); o[7] += bfhi(v.w);
        }
#pragma unroll
        for (int c = 0; c < 4; c++) {
          const int row = g + 8 * (c & 1), w = cw + 4 * (c >> 1);
          const uint32_t sw = stile[row * SPITCH + w];
          const uint32_t p = hadd2_bf16(pack_bf16(0.5f * o[2 * c], 0.5f * o[2 * c + 1]), xs[16 * SPITCH + w]);
          const float oa = bflo(p), ob = bfhi(p);
          const uint32_t gg = pack_bf16(__fdividef(oa, 1.0f + __expf(-oa)), __fdividef(ob, 1.0f + __expf(-ob)));
          const uint32_t sg = pack_bf16(bflo(sw) * bflo(gg), bfhi(sw) * bfhi(gg));
          reinterpret_cast<uint32_t*>(out)[(size_t)(s0 + row) * 256 + w] = hadd2_bf16(xs[row * SPITCH + w], sg);
        }
        if (tid == 0) TS(20 + jq);
      }
    }
  }
}

typedef CUresult (*EncodeFn)(CUtensorMap*, CUtensorMapDataType, cuuint32_t, void*, const cuuint64_t*, const cuuint64_t*,
                             const cuuint32_t*, const cuuint32_t*, CUtensorMapInterleave, CUtensorMapSwizzle,
                             CUtensorMapL2promotion, CUtensorMapFloatOOBfill);

}

extern "C" void kernel_launch(void* const* d_in, const int* in_sizes, int n_in, void* d_out, int out_size) {
  const __nv_bfloat16* x = (const __nv_bfloat16*)d_in[0];
  const __nv_bfloat16* wr = (const __nv_bfloat16*)d_in[1];
  const __nv_bfloat16* wi = (const __nv_bfloat16*)d_in[2];
  const __nv_bfloat16* w1 = (const __nv_bfloat16*)d_in[4];
  const __nv_bfloat16* b1 = (const __nv_bfloat16*)d_in[5];
  const __nv_bfloat16* w2 = (const __nv_bfloat16*)d_in[6];
  const __nv_bfloat16* b2 = (const __nv_bfloat16*)d_in[7];
  __nv_bfloat16* out = (__nv_bfloat16*)d_out;

  static EncodeFn enc = nullptr;
  static void* p_spec = nullptr;
  static void* p_wt = nullptr;
  if (!enc) {
    void* fn = nullptr;
    cudaDriverEntryPointQueryResult qr;
    cudaGetDriverEntryPoint("cuTensorMapEncodeTiled", &fn, cudaEnableDefault, &qr);
    enc = (EncodeFn)fn;
    cudaFuncSetAttribute(k_mega, cudaFuncAttributeMaxDynamicSharedMemorySize, SM_TOTAL);
    cudaGetSymbolAddress(&p_spec, g_spec);
    cudaGetSymbolAddress(&p_wt, g_wt);
  }
  Maps m;
  const cuuint32_t es[3] = {1, 1, 1};
  {
    cuuint64_t dims[3] = {(cuuint64_t)D_, (cuuint64_t)S_, 1};
    cuuint64_t strides[2] = {(cuuint64_t)D_ * 2, (cuuint64_t)D_ * 2 * S_};
    cuuint32_t box[3] = {64, 128, 1};
    enc(&m.x, CU_TENSOR_MAP_DATA_TYPE_BFLOAT16, 3, (void*)x, dims, strides, box, es, CU_TENSOR_MAP_INTERLEAVE_NONE,
        CU_TENSOR_MAP_SWIZZLE_128B, CU_TENSOR_MAP_L2_PROMOTION_L2_128B, CU_TENSOR_MAP_FLOAT_OOB_FILL_NONE);
  }
  {
    cuuint64_t dims[3] = {32, 512, 56};
    cuuint64_t strides[2] = {(cuuint64_t)F_ * 2, 64};
    cuuint32_t box[3] = {32, 32, 7};
    enc(&m.w1, CU_TENSOR_MAP_DATA_TYPE_BFLOAT16, 3, (void*)w1, dims, strides, box, es, CU_TENSOR_MAP_INTERLEAVE_NONE,
        CU_TENSOR_MAP_SWIZZLE_64B, CU_TENSOR_MAP_L2_PROMOTION_L2_128B, CU_TENSOR_MAP_FLOAT_OOB_FILL_NONE);
  }
  {
    cuuint64_t dims[3] = {(cuuint64_t)D_, (cuuint64_t)F_, 1};
    cuuint64_t strides[2] = {(cuuint64_t)D_ * 2, (cuuint64_t)D_ * 2 * F_};
    cuuint32_t box[3] = {64, 112, 1};
    enc(&m.w2, CU_TENSOR_MAP_DATA_TYPE_BFLOAT16, 3, (void*)w2, dims, strides, box, es, CU_TENSOR_MAP_INTERLEAVE_NONE,
        CU_TENSOR_MAP_SWIZZLE_128B, CU_TENSOR_MAP_L2_PROMOTION_L2_128B, CU_TENSOR_MAP_FLOAT_OOB_FILL_NONE);
  }
  {
    cuuint64_t dims[2] = {(cuuint64_t)S_, 256};
    cuuint64_t strides[1] = {(cuuint64_t)S_ * 8};
    cuuint32_t box[2] = {16, 256};
    enc(&m.spec, CU_TENSOR_MAP_DATA_TYPE_FLOAT64, 2, p_spec, dims, strides, box, es, CU_TENSOR_MAP_INTERLEAVE_NONE,
        CU_TENSOR_MAP_SWIZZLE_128B, CU_TENSOR_MAP_L2_PROMOTION_NONE, CU_TENSOR_MAP_FLOAT_OOB_FILL_NONE);
  }
  {
    cuuint64_t dims[2] = {(cuuint64_t)S_, 257};
    cuuint64_t strides[1] = {(cuuint64_t)S_ * 4};
    cuuint32_t box[2] = {16, 32};
    enc(&m.wt, CU_TENSOR_MAP_DATA_TYPE_UINT32, 2, p_wt, dims, strides, box, es, CU_TENSOR_MAP_INTERLEAVE_NONE,
        CU_TENSOR_MAP_SWIZZLE_64B, CU_TENSOR_MAP_L2_PROMOTION_NONE, CU_TENSOR_MAP_FLOAT_OOB_FILL_NONE);
  }
  k_mega<<<129, NTHREADS, SM_TOTAL>>>(x, wr, wi, w1, b1, b2, out, m);
}
```

```cpp
#include <cuda_runtime.h>
#include <cuda_bf16.h>
#include <cuda.h>
#include <stdint.h>

namespace {

constexpr int S_ = 2048, D_ = 512, F_ = 1792, DF_ = 257;
constexpr int FC = 224;
constexpr int NJOB = 4;

__device__ __align__(1024) float2 g_spec[257 * 2048];
__device__ __align__(1024) uint32_t g_wt[257 * 2048];
__device__ uint4 g_part[16 * NJOB * 8 * 8 * 256];
__device__ float2 g_cs[8 * 32 * 112];
__device__ float2 g_stats[2048];
__device__ unsigned g_bar[2];
__device__ unsigned g_flag[16 * NJOB * 8];
#define TS(i)

__device__ __forceinline__ uint32_t smem_u32(const void* p) { return (uint32_t)__cvta_generic_to_shared(p); }
__device__ __forceinline__ float bf16r(float x) { return __bfloat162float(__float2bfloat16_rn(x)); }
__device__ __forceinline__ float bflo(uint32_t w) { return __uint_as_float(w << 16); }
__device__ __forceinline__ float bfhi(uint32_t w) { return __uint_as_float(w & 0xffff0000u); }
__device__ __forceinline__ uint32_t pack_bf16(float lo, float hi) {
  uint32_t r;
  asm("cvt.rn.bf16x2.f32 %0, %1, %2;" : "=r"(r) : "f"(hi), "f"(lo));
  return r;
}
__device__ __forceinline__ uint32_t hadd2_bf16(uint32_t a, uint32_t b) {
  uint32_t r;
  asm("add.rn.bf16x2 %0, %1, %2;" : "=r"(r) : "r"(a), "r"(b));
  return r;
}
__device__ __forceinline__ void named_bar(int id, int n) { asm volatile("bar.sync %0, %1;" ::"r"(id), "r"(n) : "memory"); }
__device__ __forceinline__ void fence_async() { asm volatile("fence.proxy.async;" ::: "memory"); }

__device__ __forceinline__ void mbar_init(uint32_t bar, int cnt) { asm volatile("mbarrier.init.shared::cta.b64 [%0], %1;" ::"r"(bar), "r"(cnt) : "memory"); }
__device__ __forceinline__ void mbar_expect_tx(uint32_t bar, uint32_t bytes) { asm volatile("mbarrier.arrive.expect_tx.shared::cta.b64 _, [%0], %1;" ::"r"(bar), "r"(bytes) : "memory"); }
__device__ __forceinline__ void mbar_arrive(uint32_t bar) { asm volatile("mbarrier.arrive.shared::cta.b64 _, [%0];" ::"r"(bar) : "memory"); }
__device__ __forceinline__ void mbar_wait(uint32_t bar, uint32_t parity) {
  asm volatile(
      "{\n.reg .pred p, q;\n.reg .u32 c;\nmov.u32 c, 0;\n"
      "MW_L%=:\nmbarrier.try_wait.parity.shared::cta.b64 p, [%0], %1, %2;\n@p bra MW_D%=;\n"
      "add.u32 c, c, 1;\nsetp.lt.u32 q, c, 131072;\n@q bra MW_L%=;\ntrap;\nMW_D%=:\n}\n"
      ::"r"(bar), "r"(parity), "r"(20000u) : "memory");
}
__device__ __forceinline__ void tma_load_3d(uint32_t dst, const CUtensorMap* map, int c0, int c1, int c2, uint32_t bar) {
  asm volatile("cp.async.bulk.tensor.3d.shared::cluster.global.mbarrier::complete_tx::bytes [%0], [%1, {%3, %4, %5}], [%2];"
               ::"r"(dst), "l"((uint64_t)map), "r"(bar), "r"(c0), "r"(c1), "r"(c2) : "memory");
}
__device__ __forceinline__ void tma_load_2d(uint32_t dst, const CUtensorMap* map, int c0, int c1, uint32_t bar) {
  asm volatile("cp.async.bulk.tensor.2d.shared::cluster.global.mbarrier::complete_tx::bytes [%0], [%1, {%3, %4}], [%2];"
               ::"r"(dst), "l"((uint64_t)map), "r"(bar), "r"(c0), "r"(c1) : "memory");
}
__device__ __forceinline__ void tma_store_2d(const CUtensorMap* map, int c0, int c1, uint32_t src) {
  asm volatile("cp.async.bulk.tensor.2d.global.shared::cta.bulk_group [%0, {%2, %3}], [%1];"
               ::"l"((uint64_t)map), "r"(src), "r"(c0), "r"(c1) : "memory");
}
__device__ __forceinline__ void tma_store_commit_wait() {
  asm volatile("cp.async.bulk.commit_group;" ::: "memory");
  asm volatile("cp.async.bulk.wait_group 0;" ::: "memory");
}
__device__ __forceinline__ void wgmma_fence() { asm volatile("wgmma.fence.sync.aligned;" ::: "memory"); }
__device__ __forceinline__ void wgmma_commit() { asm volatile("wgmma.commit_group.sync.aligned;" ::: "memory"); }
template <int N> __device__ __forceinline__ void wgmma_wait() { asm volatile("wgmma.wait_group.sync.aligned %0;" ::"n"(N) : "memory"); }
__device__ __forceinline__ uint64_t make_desc(uint32_t addr, uint32_t lbo_bytes, uint32_t sbo_bytes, uint32_t swz) {
  uint64_t d = 0;
  d |= (uint64_t)((addr & 0x3FFFF) >> 4);
  d |= (uint64_t)((lbo_bytes & 0x3FFFF) >> 4) << 16;
  d |= (uint64_t)((sbo_bytes & 0x3FFFF) >> 4) << 32;
  d |= (uint64_t)swz << 62;
  return d;
}
__device__ __forceinline__ unsigned ld_acquire(const unsigned* p) {
  unsigned v;
  asm volatile("ld.acquire.gpu.global.u32 %0, [%1];" : "=r"(v) : "l"(p) : "memory");
  return v;
}

__device__ __forceinline__ void wgmma_n224_ss(float (&d)[112], uint64_t da, uint64_t db, int scale_d) {
  asm volatile("{\n.reg .pred p;\nsetp.ne.b32 p, %114, 0;\n"
    "wgmma.mma_async.sync.aligned.m64n224k16.f32.bf16.bf16 {%0, %1, %2, %3, %4, %5, %6, %7, %8, %9, %10, %11, %12, %13, %14, %15, %16, %17, %18, %19, %20, %21, %22, %23, %24, %25, %26, %27, %28, %29, %30, %31, %32, %33, %34, %35, %36, %37, %38, %39, %40, %41, %42, %43, %44, %45, %46, %47, %48, %49, %50, %51, %52, %53, %54, %55, %56, %57, %58, %59, %60, %61, %62, %63, %64, %65, %66, %67, %68, %69, %70, %71, %72, %73, %74, %75, %76, %77, %78, %79, %80, %81, %82, %83, %84, %85, %86, %87, %88, %89, %90, %91, %92, %93, %94, %95, %96, %97, %98, %99, %100, %101, %102, %103, %104, %105, %106, %107, %108, %109, %110, %111}, %112, %113, p, 1, 1, 0, 1;\n}\n"
    : "+f"(d[0]), "+f"(d[1]), "+f"(d[2]), "+f"(d[3]), "+f"(d[4]), "+f"(d[5]), "+f"(d[6]), "+f"(d[7]), "+f"(d[8]), "+f"(d[9]), "+f"(d[10]), "+f"(d[11]), "+f"(d[12]), "+f"(d[13]), "+f"(d[14]), "+f"(d[15]), "+f"(d[16]), "+f"(d[17]), "+f"(d[18]), "+f"(d[19]), "+f"(d[20]), "+f"(d[21]), "+f"(d[22]), "+f"(d[23]), "+f"(d[24]), "+f"(d[25]), "+f"(d[26]), "+f"(d[27]), "+f"(d[28]), "+f"(d[29]), "+f"(d[30]), "+f"(d[31]), "+f"(d[32]), "+f"(d[33]), "+f"(d[34]), "+f"(d[35]), "+f"(d[36]), "+f"(d[37]), "+f"(d[38]), "+f"(d[39]), "+f"(d[40]), "+f"(d[41]), "+f"(d[42]), "+f"(d[43]), "+f"(d[44]), "+f"(d[45]), "+f"(d[46]), "+f"(d[47]), "+f"(d[48]), "+f"(d[49]), "+f"(d[50]), "+f"(d[51]), "+f"(d[52]), "+f"(d[53]), "+f"(d[54]), "+f"(d[55]), "+f"(d[56]), "+f"(d[57]), "+f"(d[58]), "+f"(d[59]), "+f"(d[60]), "+f"(d[61]), "+f"(d[62]), "+f"(d[63]), "+f"(d[64]), "+f"(d[65]), "+f"(d[66]), "+f"(d[67]), "+f"(d[68]), "+f"(d[69]), "+f"(d[70]), "+f"(d[71]), "+f"(d[72]), "+f"(d[73]), "+f"(d[74]), "+f"(d[75]), "+f"(d[76]), "+f"(d[77]), "+f"(d[78]), "+f"(d[79]), "+f"(d[80]), "+f"(d[81]), "+f"(d[82]), "+f"(d[83]), "+f"(d[84]), "+f"(d[85]), "+f"(d[86]), "+f"(d[87]), "+f"(d[88]), "+f"(d[89]), "+f"(d[90]), "+f"(d[91]), "+f"(d[92]), "+f"(d[93]), "+f"(d[94]), "+f"(d[95]), "+f"(d[96]), "+f"(d[97]), "+f"(d[98]), "+f"(d[99]), "+f"(d[100]), "+f"(d[101]), "+f"(d[102]), "+f"(d[103]), "+f"(d[104]), "+f"(d[105]), "+f"(d[106]), "+f"(d[107]), "+f"(d[108]), "+f"(d[109]), "+f"(d[110]), "+f"(d[111])
    : "l"(da), "l"(db), "r"(scale_d));
}
__device__ __forceinline__ void wgmma_n128_rs(float (&d)[64], uint32_t a0, uint32_t a1, uint32_t a2, uint32_t a3, uint64_t db, int scale_d) {
  asm volatile("{\n.reg .pred p;\nsetp.ne.b32 p, %69, 0;\n"
    "wgmma.mma_async.sync.aligned.m64n128k16.f32.bf16.bf16 {%0, %1, %2, %3, %4, %5, %6, %7, %8, %9, %10, %11, %12, %13, %14, %15, %16, %17, %18, %19, %20, %21, %22, %23, %24, %25, %26, %27, %28, %29, %30, %31, %32, %33, %34, %35, %36, %37, %38, %39, %40, %41, %42, %43, %44, %45, %46, %47, %48, %49, %50, %51, %52, %53, %54, %55, %56, %57, %58, %59, %60, %61, %62, %63}, {%64, %65, %66, %67}, %68, p, 1, 1, 1;\n}\n"
    : "+f"(d[0]), "+f"(d[1]), "+f"(d[2]), "+f"(d[3]), "+f"(d[4]), "+f"(d[5]), "+f"(d[6]), "+f"(d[7]), "+f"(d[8]), "+f"(d[9]), "+f"(d[10]), "+f"(d[11]), "+f"(d[12]), "+f"(d[13]), "+f"(d[14]), "+f"(d[15]), "+f"(d[16]), "+f"(d[17]), "+f"(d[18]), "+f"(d[19]), "+f"(d[20]), "+f"(d[21]), "+f"(d[22]), "+f"(d[23]), "+f"(d[24]), "+f"(d[25]), "+f"(d[26]), "+f"(d[27]), "+f"(d[28]), "+f"(d[29]), "+f"(d[30]), "+f"(d[31]), "+f"(d[32]), "+f"(d[33]), "+f"(d[34]), "+f"(d[35]), "+f"(d[36]), "+f"(d[37]), "+f"(d[38]), "+f"(d[39]), "+f"(d[40]), "+f"(d[41]), "+f"(d[42]), "+f"(d[43]), "+f"(d[44]), "+f"(d[45]), "+f"(d[46]), "+f"(d[47]), "+f"(d[48]), "+f"(d[49]), "+f"(d[50]), "+f"(d[51]), "+f"(d[52]), "+f"(d[53]), "+f"(d[54]), "+f"(d[55]), "+f"(d[56]), "+f"(d[57]), "+f"(d[58]), "+f"(d[59]), "+f"(d[60]), "+f"(d[61]), "+f"(d[62]), "+f"(d[63])
    : "r"(a0), "r"(a1), "r"(a2), "r"(a3), "l"(db), "r"(scale_d));
}

__device__ __forceinline__ float2 cadd(float2 a, float2 b) { return make_float2(a.x + b.x, a.y + b.y); }
__device__ __forceinline__ float2 csub(float2 a, float2 b) { return make_float2(a.x - b.x, a.y - b.y); }
__device__ __forceinline__ float2 cmul(float2 a, float2 b) { return make_float2(a.x * b.x - a.y * b.y, a.x * b.y + a.y * b.x); }
__device__ __forceinline__ float2 cconj(float2 a) { return make_float2(a.x, -a.y); }

template <int DIR> __device__ __forceinline__ void dft4(float2& a0, float2& a1, float2& a2, float2& a3) {
  float2 t0 = cadd(a0, a2), t1 = csub(a0, a2), t2 = cadd(a1, a3), t3 = csub(a1, a3);
  float2 t3r = DIR < 0 ? make_float2(t3.y, -t3.x) : make_float2(-t3.y, t3.x);
  a0 = cadd(t0, t2); a2 = csub(t0, t2); a1 = cadd(t1, t3r); a3 = csub(t1, t3r);
}
template <int DIR> __device__ __forceinline__ float2 mulw(float2 v, float c, float s) {
  return DIR < 0 ? make_float2(v.x * c + v.y * s, v.y * c - v.x * s) : make_float2(v.x * c - v.y * s, v.y * c + v.x * s);
}
template <int DIR> __device__ __forceinline__ float2 muli(float2 v) {
  return DIR < 0 ? make_float2(v.y, -v.x) : make_float2(-v.y, v.x);
}
#define O16(k) (4 * ((k) & 3) + ((k) >> 2))
#define O8(k) (2 * ((k) & 3) + ((k) >> 2))
template <int DIR> __device__ __forceinline__ void dft16(float2 (&v)[16]) {
  constexpr float C1 = 0.92387953251128674f, S1 = 0.38268343236508977f, R = 0.70710678118654752f;
#pragma unroll
  for (int n2 = 0; n2 < 4; n2++) dft4<DIR>(v[n2], v[4 + n2], v[8 + n2], v[12 + n2]);
  v[5] = mulw<DIR>(v[5], C1, S1);
  v[6] = mulw<DIR>(v[6], R, R);
  v[7] = mulw<DIR>(v[7], S1, C1);
  v[9] = mulw<DIR>(v[9], R, R);
  v[10] = muli<DIR>(v[10]);
  v[11] = mulw<DIR>(v[11], -R, R);
  v[13] = mulw<DIR>(v[13], S1, C1);
  v[14] = mulw<DIR>(v[14], -R, R);
  v[15] = mulw<DIR>(v[15], -C1, -S1);
#pragma unroll
  for (int k1 = 0; k1 < 4; k1++) dft4<DIR>(v[4 * k1], v[4 * k1 + 1], v[4 * k1 + 2], v[4 * k1 + 3]);
}
template <int DIR> __device__ __forceinline__ void dft8(float2 (&v)[8]) {
  constexpr float R = 0.70710678118654752f;
  dft4<DIR>(v[0], v[2], v[4], v[6]);
  dft4<DIR>(v[1], v[3], v[5], v[7]);
  v[3] = mulw<DIR>(v[3], R, R);
  v[5] = muli<DIR>(v[5]);
  v[7] = mulw<DIR>(v[7], -R, R);
#pragma unroll
  for (int k1 = 0; k1 < 4; k1++) {
    float2 a = v[2 * k1], b = v[2 * k1 + 1];
    v[2 * k1] = cadd(a, b); v[2 * k1 + 1] = csub(a, b);
  }
}
template <int N> __device__ __forceinline__ float2 twcs(int m) {
  m &= (N - 1);
  if (m >= N / 2) m -= N;
  float s, c;
  __sincosf((float)m * (6.283185307179586f / N), &s, &c);
  return make_float2(c, s);
}

__device__ __forceinline__ void twiddle16(float2 (&v)[16], int m) {
  const float2 w1 = twcs<2048>(m);
  float2 w = w1;
#pragma unroll
  for (int k = 1; k < 16; k++) {
    v[O16(k)] = mulw<-1>(v[O16(k)], w.x, w.y);
    if (k < 15) w = cmul(w, w1);
  }
}
__device__ __forceinline__ float2* tile_at(uint8_t* tile, int k, int r) {
  return reinterpret_cast<float2*>(tile + k * 128 + ((((r >> 1) ^ k) & 7) << 4) + (r & 1) * 8);
}
constexpr int SPITCH = 260;

constexpr int STEP = 45056;
constexpr int W1_STAGE = 14336;
constexpr int SM_FFT = 184 * 1024;
constexpr int SM_WT = SM_FFT + 32768;
constexpr int SM_BAR = SM_WT + 8192;
constexpr int SM_TAB = SM_BAR + 256;
constexpr int SM_TOTAL = SM_TAB + 1280;
constexpr int NTHREADS = 384;

__device__ __forceinline__ float gelu2(float x) {
  float u = x * (0.7978845608028654f + 0.035677408136300125f * x * x);
  float th;
  asm("tanh.approx.f32 %0, %1;" : "=f"(th) : "f"(u));
  return fmaf(x, th, x);
}
__device__ __forceinline__ unsigned grid_arrive(unsigned* cnt) {
  __threadfence();
  unsigned old = atomicAdd(cnt, 1u);
  return (old / 129u + 1u) * 129u;
}
__device__ __forceinline__ void grid_wait(const unsigned* cnt, unsigned target) {
  int it = 0;
  while ((int)(ld_acquire(cnt) - target) < 0) {
    if (++it > (1 << 22)) __trap();
  }
}
__device__ __forceinline__ uint32_t piece_off(int p) {
  if (p >= 12) p -= 12;
  const int s = (p * 11) >> 5;
  return (uint32_t)(s * STEP + (p - 3 * s) * W1_STAGE);
}

struct Maps { CUtensorMap x, w1, w2, spec, wt; };

__device__ __forceinline__ void issue_items(const uint8_t* smem, int first, int n) {
#pragma unroll 1
  for (int i = first; i < first + n; i++) {
    const uint4 a = *reinterpret_cast<const uint4*>(smem + SM_TAB + i * 32);
    const uint4 c = *reinterpret_cast<const uint4*>(smem + SM_TAB + i * 32 + 16);
    if (c.w) mbar_expect_tx(a.w, c.w);
    tma_load_3d(a.z, reinterpret_cast<const CUtensorMap*>((uint64_t)a.x | ((uint64_t)a.y << 32)), (int)c.x, (int)c.y, (int)c.z, a.w);
  }
}

__device__ __forceinline__ void gemm_part(uint8_t* smem, const Maps& maps, const __nv_bfloat16* __restrict__ b1, int rt, int sp) {
  const uint32_t sb = smem_u32(smem);
  const int tid = threadIdx.x, warp = tid >> 5, lane = tid & 31, wg = warp >> 2;
  const uint32_t bar_full1 = sb + SM_BAR, bar_full2 = sb + SM_BAR + 64;
  unsigned* relcnt = reinterpret_cast<unsigned*>(smem + SM_BAR + 128);
  const uint32_t bar_stats = sb + SM_BAR + 160, bar_st = sb + SM_BAR + 224;
  uint32_t ha[56];
      auto release = [&](int j) {
        __syncwarp();
        if (lane == 0) {
          __threadfence_block();
          if ((atomicAdd(&relcnt[j & 3], 1u) & 7u) == 7u) {
            __threadfence_block();
            issue_items(smem, 3 * j + 12, 3);
          }
        }
      };
      {
        float acc[112];
#pragma unroll
        for (int i = 0; i < 112; i++) acc[i] = 0.f;
        const uint64_t dA = make_desc(sb + __shfl_sync(0xffffffffu, wg, 0) * 8192, 16, 1024, 1), dB = make_desc(sb + 16384, 2048, 512, 2);
#pragma unroll 1
        for (int j = 0; j < 8; j++) {
          const uint32_t base = (j & 3) * STEP;
          mbar_wait(bar_full1 + 8 * (j & 3), j >> 2);
          if (tid == 0 && j == 0) TS(24);
          wgmma_fence();
#pragma unroll
          for (int kk = 0; kk < 4; kk++)
            wgmma_n224_ss(acc, dA + ((base + kk * 32) >> 4), dB + ((base + (kk >> 1) * W1_STAGE + (kk & 1) * 1024) >> 4), 1);
          wgmma_commit();
          if (j > 0) {
            wgmma_wait<1>();
            release(j - 1);
          }
        }
        mbar_wait(bar_stats, 0);
        if (tid < 224) {
          float c0 = 0.f, c1 = 0.f;
          const float2* pc = g_cs + (sp * 32 + (tid & 1) * 16) * 112 + (tid >> 1);
#pragma unroll
          for (int i = 0; i < 16; i++) { const float2 c = __ldcg(pc + i * 112); c0 += c.x; c1 += c.y; }
          c0 += __shfl_xor_sync(0xffffffffu, c0, 1); c1 += __shfl_xor_sync(0xffffffffu, c1, 1);
          const uint32_t bw = __ldg(reinterpret_cast<const uint32_t*>(b1 + sp * FC) + (tid >> 1));
          reinterpret_cast<float4*>(smem + SM_WT)[tid >> 1] = make_float4(c0, c1, bflo(bw), bfhi(bw));
        }
        const int row = rt * 128 + warp * 16 + (lane >> 2);
        const float2 st0 = __ldcg(&g_stats[row]), st1 = __ldcg(&g_stats[row + 8]);
        wgmma_wait<0>();
        if (tid == 0) TS(2);
        named_bar(1, 256);
        if (tid == 0) {
          issue_items(smem, 33, 3);
        }
        const float4* csb = reinterpret_cast<const float4*>(smem + SM_WT) + (lane & 3);
#pragma unroll
        for (int j = 0; j < 28; j++) {
          const float4 c = csb[j * 4];
          ha[2 * j] = pack_bf16(gelu2(fmaf(fmaf(-st0.x, c.x, acc[4 * j]), st0.y, c.z)), gelu2(fmaf(fmaf(-st0.x, c.y, acc[4 * j + 1]), st0.y, c.w)));
          ha[2 * j + 1] = pack_bf16(gelu2(fmaf(fmaf(-st1.x, c.x, acc[4 * j + 2]), st1.y, c.z)), gelu2(fmaf(fmaf(-st1.x, c.y, acc[4 * j + 3]), st1.y, c.w)));
        }
      }
      if (tid == 0) TS(4);
      if (wg == 1) named_bar(2, 256);
#pragma unroll 1
      for (int jq = 0; jq < NJOB; jq++) {
        float acc[64];
#pragma unroll
        for (int h = 0; h < 2; h++) {
          const uint32_t o0 = piece_off(4 * jq + 2 * h), o1 = piece_off(4 * jq + 2 * h + 1);
          const uint64_t dW = make_desc(sb + o0, o1 - o0, 1024, 1);
          mbar_wait(bar_full2 + 8 * (2 * jq + h), 0);
          wgmma_fence();
#pragma unroll
          for (int kk = 0; kk < 7; kk++) {
            const int kb = h * 7 + kk;
            wgmma_n128_rs(acc, ha[4 * kb], ha[4 * kb + 1], ha[4 * kb + 2], ha[4 * kb + 3], dW + kk * 128, kb > 0);
          }
          wgmma_commit();
        }
        if (jq == 0 && wg == 0) asm volatile("bar.arrive 2, 256;" ::: "memory");
        wgmma_wait<0>();
        if (jq == 0 && lane == 0) {
          __threadfence_block();
          if (atomicAdd(&relcnt[4], 1u) == 7u) {
            __threadfence_block();
            issue_items(smem, 36, 4);
          }
        }
        uint4* dstp = g_part + ((((size_t)rt * NJOB + jq) * 8 + warp) * 8 + sp) * 256 + lane;
#pragma unroll
        for (int i = 0; i < 8; i++)
          dstp[i * 32] = make_uint4(pack_bf16(acc[8 * i], acc[8 * i + 1]), pack_bf16(acc[8 * i + 2], acc[8 * i + 3]),
                                    pack_bf16(acc[8 * i + 4], acc[8 * i + 5]), pack_bf16(acc[8 * i + 6], acc[8 * i + 7]));
        __syncwarp();
        if (lane == 0) mbar_arrive(bar_st + 8 * jq);
        if (tid == 0 && jq == 3) TS(8);
      }
}

__global__ void __launch_bounds__(NTHREADS, 1)
k_mega(const __nv_bfloat16* __restrict__ x, const __nv_bfloat16* __restrict__ wr, const __nv_bfloat16* __restrict__ wi,
       const __nv_bfloat16* __restrict__ w1, const __nv_bfloat16* __restrict__ b1, const __nv_bfloat16* __restrict__ b2, __nv_bfloat16* __restrict__ out,
       const __grid_constant__ Maps maps) {
  extern __shared__ __align__(1024) uint8_t smem[];
  const uint32_t sb = smem_u32(smem);
  const int rt = blockIdx.x >> 3, sp = blockIdx.x & 7;
  const int warp = threadIdx.x >> 5, lane = threadIdx.x & 31;
  const int s0 = blockIdx.x * 16;
  if (threadIdx.x == 0) TS(0);
  const uint32_t bar_full1 = sb + SM_BAR;
  const uint32_t bar_full2 = sb + SM_BAR + 64;
  unsigned* relcnt = reinterpret_cast<unsigned*>(smem + SM_BAR + 128);
  const uint32_t bar_stats = sb + SM_BAR + 160;
  const uint32_t bar_p1 = sb + SM_BAR + 168;
  const uint32_t bar_tile = sb + SM_BAR + 176;
  const uint32_t bar_pre = sb + SM_BAR + 184;
  const uint32_t bar_st = sb + SM_BAR + 224;
  const uint32_t bar_g = sb + SM_BAR + 192;
  uint8_t* tile = smem + SM_FFT;

  if (threadIdx.x == 0) {
    for (int i = 0; i < 4; i++) mbar_init(bar_full1 + 8 * i, 1);
    for (int i = 0; i < 8; i++) mbar_init(bar_full2 + 8 * i, 2);
    mbar_init(bar_stats, 1); mbar_init(bar_p1, 1); mbar_init(bar_pre, 128); mbar_init(bar_tile, 1);
    for (int i = 0; i < 4; i++) { mbar_init(bar_g + 8 * i, 1); mbar_init(bar_st + 8 * i, 8); }
    for (int i = 0; i < 5; i++) relcnt[i] = 0;
    asm volatile("fence.mbarrier_init.release.cluster;" ::: "memory");
  }
  if (warp == 1) {
#pragma unroll 1
    for (int i = lane; i < 40; i += 32) {
      uint64_t mp; uint32_t dst, bar, bytes; int c0, c1, c2;
      if (i < 24) {
        const int j = (i * 11) >> 5, part = i - 3 * j;
        bar = bar_full1 + 8 * (j & 3);
        bytes = part ? 0 : STEP;
        dst = sb + (j & 3) * STEP + (part ? 16384 + (part - 1) * W1_STAGE : 0);
        mp = (uint64_t)(part ? &maps.w1 : &maps.x);
        c0 = part ? 0 : j * 64; c1 = part ? j * 64 + (part - 1) * 32 : rt * 128; c2 = part ? sp * 7 : 0;
      } else {
        const int p = i - 24;
        bar = bar_full2 + 8 * (p >> 1);
        bytes = W1_STAGE;
        dst = sb + piece_off(p);
        mp = (uint64_t)&maps.w2;
        c0 = (p >> 2) * 128 + (p & 1) * 64; c1 = sp * FC + ((p >> 1) & 1) * 112; c2 = 0;
      }
      *reinterpret_cast<uint4*>(smem + SM_TAB + i * 32) = make_uint4((uint32_t)mp, (uint32_t)(mp >> 32), dst, bar);
      *reinterpret_cast<uint4*>(smem + SM_TAB + i * 32 + 16) = make_uint4(c0, c1, c2, bytes);
    }
  }
  __syncthreads();
  if (threadIdx.x == 32 && blockIdx.x < 128) issue_items(smem, 0, 12);

  if (warp >= 8) {
    const int t = threadIdx.x & 127;
    const bool extra = blockIdx.x == 128;
    if (!extra) {
      const uint32_t stg = (uint32_t)(SM_WT + (warp - 8) * 2048);
      if (t < 16) {
        const size_t o = (size_t)(s0 + t) * DF_ + 256;
        g_wt[(size_t)256 * S_ + s0 + t] = (uint32_t)__ldg(reinterpret_cast<const unsigned short*>(wr) + o) |
                                          ((uint32_t)__ldg(reinterpret_cast<const unsigned short*>(wi) + o) << 16);
      }
      uint32_t wv[2][16];
      {
        const unsigned short* pr = reinterpret_cast<const unsigned short*>(wr) + (size_t)s0 * DF_ + t;
        const unsigned short* pi = reinterpret_cast<const unsigned short*>(wi) + (size_t)s0 * DF_ + t;
#pragma unroll
        for (int u = 0; u < 32; u++)
          wv[u >> 4][u & 15] = (uint32_t)__ldg(pr + (u & 15) * DF_ + (u >> 4) * 128) | ((uint32_t)__ldg(pi + (u & 15) * DF_ + (u >> 4) * 128) << 16);
      }
#pragma unroll
      for (int rd = 0; rd < 2; rd++) {
        if (rd && lane == 0) asm volatile("cp.async.bulk.wait_group.read 0;" ::: "memory");
        __syncwarp();
#pragma unroll
        for (int c = 0; c < 4; c++)
          *reinterpret_cast<uint4*>(smem + stg + lane * 64 + ((c ^ ((lane >> 1) & 3)) << 4)) =
              make_uint4(wv[rd][4 * c], wv[rd][4 * c + 1], wv[rd][4 * c + 2], wv[rd][4 * c + 3]);
        fence_async();
        __syncwarp();
        if (lane == 0) {
          tma_store_2d(&maps.wt, s0, rd * 128 + (warp - 8) * 32, sb + stg);
          asm volatile("cp.async.bulk.commit_group;" ::: "memory");
        }
      }
      if (lane == 0) { asm volatile("cp.async.bulk.wait_group 0;" ::: "memory"); __threadfence(); }
    }
#pragma unroll 1
    for (int ph = 0; ph < 2; ph++) {
    if (ph == 0 && !extra) mbar_wait(bar_p1, 0);
    if (!extra) {
      const int r = t & 15;
      const float y256 = ph ? __ldcg(&g_spec[(size_t)256 * S_ + s0 + r]).x : 0.f;
      const float sg = ph ? 1.f : -1.f, sc = ph ? 1.f : 0.5f;
      float2 tw = twcs<512>(t >> 4);
#pragma unroll 2
      for (int j = t >> 4; j < 128; j += 8) {
        float2* pa = tile_at(tile, j, r);
        float2* pb = tile_at(tile, j == 0 ? 128 : 256 - j, r);
        const float2 A = *pa, B = *pb;
        const float2 P = make_float2(sc * (A.x + B.x), sc * (A.y - B.y)), M = make_float2(sc * (A.x - B.x), sc * (A.y + B.y));
        const float ts = sg * tw.y;
        const float2 T = make_float2(M.x * tw.x - M.y * ts, M.y * tw.x + M.x * ts);
        tw = cmul(tw, make_float2(0.99518472667219689f, 0.09801714032956060f));
        const float2 V = make_float2(-sg * T.y, sg * T.x);
        if (j) {
          *pa = make_float2(P.x + V.x, -sg * (P.y + V.y));
          *pb = make_float2(P.x - V.x, sg * (P.y - V.y));
        } else if (ph == 0) {
          g_spec[(size_t)256 * S_ + s0 + r] = make_float2(A.x - A.y, 0.f);
          *pa = make_float2(A.x + A.y, 0.f);
          *pb = cconj(B);
        } else {
          *pa = make_float2(A.x + y256, y256 - A.x);
          *pb = make_float2(2.f * B.x, 2.f * B.y);
        }
      }
    }
    if (ph) { mbar_arrive(bar_pre); break; }
    fence_async();
    named_bar(3, 128);
    if (t == 0) {
      if (!extra) {
        tma_store_2d(&maps.spec, s0, 0, sb + SM_FFT);
        tma_store_commit_wait();
      }
      const unsigned target = grid_arrive(&g_bar[0]);
      grid_wait(&g_bar[0], target);
      mbar_arrive(bar_stats);
    }
    named_bar(3, 128);
    if (t == 0) TS(13);
    {
      float2* buf = reinterpret_cast<float2*>(tile);
      const int k1 = t >> 3, m2 = t & 7;
      const int c0 = extra ? 256 : blockIdx.x * 2, nc = extra ? 1 : 2;
      float2 vn[16];
      uint32_t wn[16];
#pragma unroll 1
      for (int c = -1; c < nc; c++) {
        uint32_t wq[16];
        if (c >= 0) {
#pragma unroll
          for (int i = 0; i < 16; i++) { buf[128 * i + t] = vn[i]; wq[i] = wn[i]; }
        }
        if (c + 1 < nc) {
#pragma unroll
          for (int i = 0; i < 16; i++) {
            vn[i] = __ldcg(g_spec + (size_t)(c0 + c + 1) * S_ + 128 * i + t);
            wn[i] = __ldcg(g_wt + (size_t)(c0 + c + 1) * S_ + 128 * i + t);
          }
        }
        if (c < 0) continue;
#pragma unroll 1
        for (int it = 0; it < 2; it++) {
#pragma unroll 1
          for (int p = 0; p < 2; p++) {
            const float2* in = buf + (p ? k1 * 136 + m2 : t);
            const int is = p ? 8 : 128;
            float2 v[16];
#pragma unroll
            for (int i = 0; i < 16; i++) v[i] = in[i * is];
            dft16<-1>(v);
            twiddle16(v, p ? 16 * m2 : t);
            named_bar(3, 128);
            float2* o = buf + (p ? k1 * 9 + m2 : t);
            const int os = p ? 144 : 136;
#pragma unroll
            for (int kk = 0; kk < 16; kk++) o[kk * os] = v[O16(kk)];
            named_bar(3, 128);
          }
          float2 e[2][8];
#pragma unroll
          for (int m = 0; m < 8; m++) { e[0][m] = buf[t * 9 + m]; e[1][m] = buf[(t + 128) * 9 + m]; }
          dft8<-1>(e[0]);
          dft8<-1>(e[1]);
          named_bar(3, 128);
          if (it == 0) {
            constexpr float SC = 1.0f / (2048.0f * 512.0f);
#pragma unroll
            for (int i = 0; i < 16; i++)
              buf[128 * i + t] = cconj(cmul(e[i & 1][O8(i >> 1)], make_float2(bflo(wq[i]) * SC, bfhi(wq[i]) * SC)));
          } else {
            float2* col = g_spec + (size_t)(c0 + c) * S_ + t;
#pragma unroll
            for (int i = 0; i < 16; i++) col[128 * i] = cconj(e[i & 1][O8(i >> 1)]);
          }
        }
      }
    }
    named_bar(3, 128);
    if (t == 0) {
      TS(14);
      const unsigned target = grid_arrive(&g_bar[1]);
      if (!extra) {
        grid_wait(&g_bar[1], target);
        TS(15);
        fence_async();
        mbar_expect_tx(bar_tile, 32768);
        tma_load_2d(sb + SM_FFT, &maps.spec, s0, 0, bar_tile);
      }
    }
    if (extra) break;
    mbar_wait(bar_tile, 0);
    }
    if (warp == 9 && lane < 8 && !extra) {
#pragma unroll 1
      for (int jq = 0; jq < NJOB; jq++) {
        mbar_wait(bar_st + 8 * jq, 0);
        __threadfence();
        atomicAdd(&g_flag[(rt * NJOB + jq) * 8 + lane], 1u);
      }
    }
    if (t == 64 && !extra) {
        mbar_wait(bar_st + 24, 0);
#pragma unroll 1
        for (int jq = 0; jq < NJOB; jq++) {
          unsigned* fl = &g_flag[(rt * NJOB + jq) * 8 + sp];
          int it = 0;
          while (ld_acquire(fl) < 8u) {
            if (++it > (1 << 22)) __trap();
          }
          *fl = 0u;
          fence_async();
          mbar_expect_tx(bar_g + 8 * jq, jq ? 32768 : 32768 + 17 * 1024);
          asm volatile("cp.async.bulk.shared::cluster.global.mbarrier::complete_tx::bytes [%0], [%1], %2, [%3];"
                       ::"r"(sb + jq * 32768), "l"(g_part + (((size_t)rt * NJOB + jq) * 8 + sp) * 8 * 256), "r"(32768), "r"(bar_g + 8 * jq) : "memory");
          if (jq == 0) {
#pragma unroll 1
            for (int i = 0; i < 17; i++)
              asm volatile("cp.async.bulk.shared::cluster.global.mbarrier::complete_tx::bytes [%0], [%1], %2, [%3];"
                           ::"r"(sb + 131072 + i * SPITCH * 4), "l"(i < 16 ? x + (size_t)(s0 + i) * D_ : b2), "r"(1024), "r"(bar_g) : "memory");
          }
        }
    }
  } else {
    if (blockIdx.x == 128) return;
    const int tid = threadIdx.x;
    const int r = tid & 15, q = tid >> 4;
#pragma unroll 1
    for (int ph = 0; ph < 2; ph++) {
      if (ph) mbar_wait(bar_pre, 0);
      if (ph == 0) {
        uint32_t w[16];
        const uint32_t* xw = reinterpret_cast<const uint32_t*>(x + (size_t)(s0 + q) * D_);
#pragma unroll
        for (int n1 = 0; n1 < 16; n1++) w[n1] = __ldg(xw + 16 * n1 + r);
        if ((tid & 127) < 112) {
          const uint32_t* pw = reinterpret_cast<const uint32_t*>(w1 + (size_t)(rt * 32 + (tid >> 7) * 16) * F_ + sp * FC) + (tid & 127);
          float c0 = 0.f, c1 = 0.f;
#pragma unroll
          for (int k = 0; k < 16; k++) { const uint32_t ww = __ldg(pw + k * (F_ / 2)); c0 += bflo(ww); c1 += bfhi(ww); }
          g_cs[(sp * 32 + rt * 2 + (tid >> 7)) * 112 + (tid & 127)] = make_float2(c0, c1);
        }
        float sum = 0.f;
#pragma unroll
        for (int n1 = 0; n1 < 16; n1++) sum += bflo(w[n1]) + bfhi(w[n1]);
#pragma unroll
        for (int o = 1; o < 16; o <<= 1) sum += __shfl_xor_sync(0xffffffffu, sum, o);
        const float mean = sum * (1.0f / D_);
        float sq = 0.f;
#pragma unroll
        for (int n1 = 0; n1 < 16; n1++) {
          float a = bflo(w[n1]) - mean, c = bfhi(w[n1]) - mean;
          sq += a * a + c * c;
        }
#pragma unroll
        for (int o = 1; o < 16; o <<= 1) sq += __shfl_xor_sync(0xffffffffu, sq, o);
        const uint32_t nm2 = pack_bf16(-mean, -mean);
        float sd, rs;
        asm("sqrt.approx.f32 %0, %1;" : "=f"(sd) : "f"(bf16r(bf16r(sq * (1.0f / D_)) + 1e-5f)));
        asm("rcp.approx.f32 %0, %1;" : "=f"(rs) : "f"(bf16r(sd)));
        if (r == 0) g_stats[s0 + q] = make_float2(-bflo(nm2), rs);
#pragma unroll
        for (int n1 = 0; n1 < 16; n1++) {
          const uint32_t d = hadd2_bf16(w[n1], nm2);
          const uint32_t xn = pack_bf16(bflo(d) * rs, bfhi(d) * rs);
          *tile_at(tile, 16 * n1 + r, q) = make_float2(bflo(xn), bfhi(xn));
        }
      }
      named_bar(1, 256);
      {
        uint8_t* pa = reinterpret_cast<uint8_t*>(tile_at(tile, q, r));
        const uint8_t* pb = tile + q * 2048 + (r & 1) * 8;
#pragma unroll 1
        for (int p = 0; p < 2; p++) {
          float2 v[16];
#pragma unroll
          for (int i = 0; i < 16; i++)
            v[i] = *reinterpret_cast<const float2*>(p ? pb + i * 128 + ((((r >> 1) ^ i) & 7) << 4) : pa + i * 2048);
          dft16<-1>(v);
          if (p == 0) twiddle16(v, 8 * q);
          named_bar(1, 256);
          if (p && ph) {
#pragma unroll
            for (int i = 0; i < 16; i++) reinterpret_cast<uint32_t*>(tile)[r * SPITCH + q + 16 * i] = pack_bf16(v[O16(i)].x, -v[O16(i)].y);
          } else {
#pragma unroll
            for (int i = 0; i < 16; i++) *reinterpret_cast<float2*>(pa + i * 2048) = v[O16(i)];
          }
          named_bar(1, 256);
        }
      }
      if (ph == 0) {
        if (tid == 0) mbar_arrive(bar_p1);
        gemm_part(smem, maps, b1, rt, sp);
      }
    }
    if (tid == 0) TS(16);
    {
      const int g = lane >> 2;
      const uint32_t* stile = reinterpret_cast<const uint32_t*>(tile);
      const uint32_t* xs = reinterpret_cast<const uint32_t*>(smem + 131072);
#pragma unroll 1
      for (int jq = 0; jq < NJOB; jq++) {
        const int cw = jq * 64 + 8 * warp + (lane & 3);
        mbar_wait(bar_g + 8 * jq, 0);
        const uint4* src = reinterpret_cast<const uint4*>(smem + jq * 32768) + tid;
        float o[8];
#pragma unroll
        for (int c = 0; c < 8; c++) o[c] = 0.f;
#pragma unroll
        for (int s = 0; s < 8; s++) {
          const uint4 v = src[s * 256];
          o[0] += bflo(v.x); o[1] += bfhi(v.x); o[2] += bflo(v.y); o[3] += bfhi(v.y);
          o[4] += bflo(v.z); o[5] += bfhi(v.z); o[6] += bflo(v.w); o[7] += bfhi(v.w);
        }
#pragma unroll
        for (int c = 0; c < 4; c++) {
          const int row = g + 8 * (c & 1), w = cw + 4 * (c >> 1);
          const uint32_t sw = stile[row * SPITCH + w];
          const uint32_t p = hadd2_bf16(pack_bf16(0.5f * o[2 * c], 0.5f * o[2 * c + 1]), xs[16 * SPITCH + w]);
          const float oa = bflo(p), ob = bfhi(p);
          const uint32_t gg = pack_bf16(__fdividef(oa, 1.0f + __expf(-oa)), __fdividef(ob, 1.0f + __expf(-ob)));
          const uint32_t sg = pack_bf16(bflo(sw) * bflo(gg), bfhi(sw) * bfhi(gg));
          reinterpret_cast<uint32_t*>(out)[(size_t)(s0 + row) * 256 + w] = hadd2_bf16(xs[row * SPITCH + w], sg);
        }
        if (tid == 0 && jq == 3) TS(23);
      }
    }
  }
}

typedef CUresult (*EncodeFn)(CUtensorMap*, CUtensorMapDataType, cuuint32_t, void*, const cuuint64_t*, const cuuint64_t*,
                             const cuuint32_t*, const cuuint32_t*, CUtensorMapInterleave, CUtensorMapSwizzle,
                             CUtensorMapL2promotion, CUtensorMapFloatOOBfill);

}

extern "C" void kernel_launch(void* const* d_in, const int* in_sizes, int n_in, void* d_out, int out_size) {
  const __nv_bfloat16* x = (const __nv_bfloat16*)d_in[0];
  const __nv_bfloat16* wr = (const __nv_bfloat16*)d_in[1];
  const __nv_bfloat16* wi = (const __nv_bfloat16*)d_in[2];
  const __nv_bfloat16* w1 = (const __nv_bfloat16*)d_in[4];
  const __nv_bfloat16* b1 = (const __nv_bfloat16*)d_in[5];
  const __nv_bfloat16* w2 = (const __nv_bfloat16*)d_in[6];
  const __nv_bfloat16* b2 = (const __nv_bfloat16*)d_in[7];
  __nv_bfloat16* out = (__nv_bfloat16*)d_out;

  static EncodeFn enc = nullptr;
  static void* p_spec = nullptr;
  static void* p_wt = nullptr;
  if (!enc) {
    void* fn = nullptr;
    cudaDriverEntryPointQueryResult qr;
    cudaGetDriverEntryPoint("cuTensorMapEncodeTiled", &fn, cudaEnableDefault, &qr);
    enc = (EncodeFn)fn;
    cudaFuncSetAttribute(k_mega, cudaFuncAttributeMaxDynamicSharedMemorySize, SM_TOTAL);
    cudaGetSymbolAddress(&p_spec, g_spec);
    cudaGetSymbolAddress(&p_wt, g_wt);
  }
  Maps m;
  const cuuint32_t es[3] = {1, 1, 1};
  {
    cuuint64_t dims[3] = {(cuuint64_t)D_, (cuuint64_t)S_, 1};
    cuuint64_t strides[2] = {(cuuint64_t)D_ * 2, (cuuint64_t)D_ * 2 * S_};
    cuuint32_t box[3] = {64, 128, 1};
    enc(&m.x, CU_TENSOR_MAP_DATA_TYPE_BFLOAT16, 3, (void*)x, dims, strides, box, es, CU_TENSOR_MAP_INTERLEAVE_NONE,
        CU_TENSOR_MAP_SWIZZLE_128B, CU_TENSOR_MAP_L2_PROMOTION_L2_128B, CU_TENSOR_MAP_FLOAT_OOB_FILL_NONE);
  }
  {
    cuuint64_t dims[3] = {32, 512, 56};
    cuuint64_t strides[2] = {(cuuint64_t)F_ * 2, 64};
    cuuint32_t box[3] = {32, 32, 7};
    enc(&m.w1, CU_TENSOR_MAP_DATA_TYPE_BFLOAT16, 3, (void*)w1, dims, strides, box, es, CU_TENSOR_MAP_INTERLEAVE_NONE,
        CU_TENSOR_MAP_SWIZZLE_64B, CU_TENSOR_MAP_L2_PROMOTION_L2_128B, CU_TENSOR_MAP_FLOAT_OOB_FILL_NONE);
  }
  {
    cuuint64_t dims[3] = {(cuuint64_t)D_, (cuuint64_t)F_, 1};
    cuuint64_t strides[2] = {(cuuint64_t)D_ * 2, (cuuint64_t)D_ * 2 * F_};
    cuuint32_t box[3] = {64, 112, 1};
    enc(&m.w2, CU_TENSOR_MAP_DATA_TYPE_BFLOAT16, 3, (void*)w2, dims, strides, box, es, CU_TENSOR_MAP_INTERLEAVE_NONE,
        CU_TENSOR_MAP_SWIZZLE_128B, CU_TENSOR_MAP_L2_PROMOTION_L2_128B, CU_TENSOR_MAP_FLOAT_OOB_FILL_NONE);
  }
  {
    cuuint64_t dims[2] = {(cuuint64_t)S_, 256};
    cuuint64_t strides[1] = {(cuuint64_t)S_ * 8};
    cuuint32_t box[2] = {16, 256};
    enc(&m.spec, CU_TENSOR_MAP_DATA_TYPE_FLOAT64, 2, p_spec, dims, strides, box, es, CU_TENSOR_MAP_INTERLEAVE_NONE,
        CU_TENSOR_MAP_SWIZZLE_128B, CU_TENSOR_MAP_L2_PROMOTION_NONE, CU_TENSOR_MAP_FLOAT_OOB_FILL_NONE);
  }
  {
    cuuint64_t dims[2] = {(cuuint64_t)S_, 257};
    cuuint64_t strides[1] = {(cuuint64_t)S_ * 4};
    cuuint32_t box[2] = {16, 32};
    enc(&m.wt, CU_TENSOR_MAP_DATA_TYPE_UINT32, 2, p_wt, dims, strides, box, es, CU_TENSOR_MAP_INTERLEAVE_NONE,
        CU_TENSOR_MAP_SWIZZLE_64B, CU_TENSOR_MAP_L2_PROMOTION_NONE, CU_TENSOR_MAP_FLOAT_OOB_FILL_NONE);
  }
  k_mega<<<129, NTHREADS, SM_TOTAL>>>(x, wr, wi, w1, b1, b2, out, m);
}
```

```cpp
#include <cuda_runtime.h>
#include <cuda_bf16.h>
#include <cuda.h>
#include <stdint.h>

namespace {

constexpr int S_ = 2048, D_ = 512, F_ = 1792, DF_ = 257;
constexpr int FC = 224;
constexpr int NJOB = 4;

__device__ __align__(1024) float2 g_spec[257 * 2048];
__device__ __align__(1024) uint32_t g_wt[257 * 2048];
__device__ uint4 g_part[16 * NJOB * 8 * 8 * 256];
__device__ float2 g_cs[8 * 32 * 112];
__device__ float2 g_stats[2048];
__device__ unsigned g_bar[2];
__device__ unsigned g_flag[16 * NJOB * 8];
#define TS(i)

__device__ __forceinline__ uint32_t smem_u32(const void* p) { return (uint32_t)__cvta_generic_to_shared(p); }
__device__ __forceinline__ float bf16r(float x) { return __bfloat162float(__float2bfloat16_rn(x)); }
__device__ __forceinline__ float bflo(uint32_t w) { return __uint_as_float(w << 16); }
__device__ __forceinline__ float bfhi(uint32_t w) { return __uint_as_float(w & 0xffff0000u); }
__device__ __forceinline__ uint32_t pack_bf16(float lo, float hi) {
  uint32_t r;
  asm("cvt.rn.bf16x2.f32 %0, %1, %2;" : "=r"(r) : "f"(hi), "f"(lo));
  return r;
}
__device__ __forceinline__ uint32_t hadd2_bf16(uint32_t a, uint32_t b) {
  uint32_t r;
  asm("add.rn.bf16x2 %0, %1, %2;" : "=r"(r) : "r"(a), "r"(b));
  return r;
}
__device__ __forceinline__ void named_bar(int id, int n) { asm volatile("bar.sync %0, %1;" ::"r"(id), "r"(n) : "memory"); }
__device__ __forceinline__ void fence_async() { asm volatile("fence.proxy.async;" ::: "memory"); }

__device__ __forceinline__ void mbar_init(uint32_t bar, int cnt) { asm volatile("mbarrier.init.shared::cta.b64 [%0], %1;" ::"r"(bar), "r"(cnt) : "memory"); }
__device__ __forceinline__ void mbar_expect_tx(uint32_t bar, uint32_t bytes) { asm volatile("mbarrier.arrive.expect_tx.shared::cta.b64 _, [%0], %1;" ::"r"(bar), "r"(bytes) : "memory"); }
__device__ __forceinline__ void mbar_arrive(uint32_t bar) { asm volatile("mbarrier.arrive.shared::cta.b64 _, [%0];" ::"r"(bar) : "memory"); }
__device__ __forceinline__ void mbar_wait(uint32_t bar, uint32_t parity) {
  asm volatile(
      "{\n.reg .pred p, q;\n.reg .u32 c;\nmov.u32 c, 0;\n"
      "MW_L%=:\nmbarrier.try_wait.parity.shared::cta.b64 p, [%0], %1, %2;\n@p bra MW_D%=;\n"
      "add.u32 c, c, 1;\nsetp.lt.u32 q, c, 131072;\n@q bra MW_L%=;\ntrap;\nMW_D%=:\n}\n"
      ::"r"(bar), "r"(parity), "r"(20000u) : "memory");
}
__device__ __forceinline__ void tma_load_3d(uint32_t dst, const CUtensorMap* map, int c0, int c1, int c2, uint32_t bar) {
  asm volatile("cp.async.bulk.tensor.3d.shared::cluster.global.mbarrier::complete_tx::bytes [%0], [%1, {%3, %4, %5}], [%2];"
               ::"r"(dst), "l"((uint64_t)map), "r"(bar), "r"(c0), "r"(c1), "r"(c2) : "memory");
}
__device__ __forceinline__ void tma_load_2d(uint32_t dst, const CUtensorMap* map, int c0, int c1, uint32_t bar) {
  asm volatile("cp.async.bulk.tensor.2d.shared::cluster.global.mbarrier::complete_tx::bytes [%0], [%1, {%3, %4}], [%2];"
               ::"r"(dst), "l"((uint64_t)map), "r"(bar), "r"(c0), "r"(c1) : "memory");
}
__device__ __forceinline__ void tma_store_2d(const CUtensorMap* map, int c0, int c1, uint32_t src) {
  asm volatile("cp.async.bulk.tensor.2d.global.shared::cta.bulk_group [%0, {%2, %3}], [%1];"
               ::"l"((uint64_t)map), "r"(src), "r"(c0), "r"(c1) : "memory");
}
__device__ __forceinline__ void tma_store_commit_wait() {
  asm volatile("cp.async.bulk.commit_group;" ::: "memory");
  asm volatile("cp.async.bulk.wait_group 0;" ::: "memory");
}
__device__ __forceinline__ void wgmma_fence() { asm volatile("wgmma.fence.sync.aligned;" ::: "memory"); }
__device__ __forceinline__ void wgmma_commit() { asm volatile("wgmma.commit_group.sync.aligned;" ::: "memory"); }
template <int N> __device__ __forceinline__ void wgmma_wait() { asm volatile("wgmma.wait_group.sync.aligned %0;" ::"n"(N) : "memory"); }
__device__ __forceinline__ uint64_t make_desc(uint32_t addr, uint32_t lbo_bytes, uint32_t sbo_bytes, uint32_t swz) {
  uint64_t d = 0;
  d |= (uint64_t)((addr & 0x3FFFF) >> 4);
  d |= (uint64_t)((lbo_bytes & 0x3FFFF) >> 4) << 16;
  d |= (uint64_t)((sbo_bytes & 0x3FFFF) >> 4) << 32;
  d |= (uint64_t)swz << 62;
  return d;
}
__device__ __forceinline__ unsigned ld_acquire(const unsigned* p) {
  unsigned v;
  asm volatile("ld.acquire.gpu.global.u32 %0, [%1];" : "=r"(v) : "l"(p) : "memory");
  return v;
}

__device__ __forceinline__ void wgmma_n224_ss(float (&d)[112], uint64_t da, uint64_t db, int scale_d) {
  asm volatile("{\n.reg .pred p;\nsetp.ne.b32 p, %114, 0;\n"
    "wgmma.mma_async.sync.aligned.m64n224k16.f32.bf16.bf16 {%0, %1, %2, %3, %4, %5, %6, %7, %8, %9, %10, %11, %12, %13, %14, %15, %16, %17, %18, %19, %20, %21, %22, %23, %24, %25, %26, %27, %28, %29, %30, %31, %32, %33, %34, %35, %36, %37, %38, %39, %40, %41, %42, %43, %44, %45, %46, %47, %48, %49, %50, %51, %52, %53, %54, %55, %56, %57, %58, %59, %60, %61, %62, %63, %64, %65, %66, %67, %68, %69, %70, %71, %72, %73, %74, %75, %76, %77, %78, %79, %80, %81, %82, %83, %84, %85, %86, %87, %88, %89, %90, %91, %92, %93, %94, %95, %96, %97, %98, %99, %100, %101, %102, %103, %104, %105, %106, %107, %108, %109, %110, %111}, %112, %113, p, 1, 1, 0, 1;\n}\n"
    : "+f"(d[0]), "+f"(d[1]), "+f"(d[2]), "+f"(d[3]), "+f"(d[4]), "+f"(d[5]), "+f"(d[6]), "+f"(d[7]), "+f"(d[8]), "+f"(d[9]), "+f"(d[10]), "+f"(d[11]), "+f"(d[12]), "+f"(d[13]), "+f"(d[14]), "+f"(d[15]), "+f"(d[16]), "+f"(d[17]), "+f"(d[18]), "+f"(d[19]), "+f"(d[20]), "+f"(d[21]), "+f"(d[22]), "+f"(d[23]), "+f"(d[24]), "+f"(d[25]), "+f"(d[26]), "+f"(d[27]), "+f"(d[28]), "+f"(d[29]), "+f"(d[30]), "+f"(d[31]), "+f"(d[32]), "+f"(d[33]), "+f"(d[34]), "+f"(d[35]), "+f"(d[36]), "+f"(d[37]), "+f"(d[38]), "+f"(d[39]), "+f"(d[40]), "+f"(d[41]), "+f"(d[42]), "+f"(d[43]), "+f"(d[44]), "+f"(d[45]), "+f"(d[46]), "+f"(d[47]), "+f"(d[48]), "+f"(d[49]), "+f"(d[50]), "+f"(d[51]), "+f"(d[52]), "+f"(d[53]), "+f"(d[54]), "+f"(d[55]), "+f"(d[56]), "+f"(d[57]), "+f"(d[58]), "+f"(d[59]), "+f"(d[60]), "+f"(d[61]), "+f"(d[62]), "+f"(d[63]), "+f"(d[64]), "+f"(d[65]), "+f"(d[66]), "+f"(d[67]), "+f"(d[68]), "+f"(d[69]), "+f"(d[70]), "+f"(d[71]), "+f"(d[72]), "+f"(d[73]), "+f"(d[74]), "+f"(d[75]), "+f"(d[76]), "+f"(d[77]), "+f"(d[78]), "+f"(d[79]), "+f"(d[80]), "+f"(d[81]), "+f"(d[82]), "+f"(d[83]), "+f"(d[84]), "+f"(d[85]), "+f"(d[86]), "+f"(d[87]), "+f"(d[88]), "+f"(d[89]), "+f"(d[90]), "+f"(d[91]), "+f"(d[92]), "+f"(d[93]), "+f"(d[94]), "+f"(d[95]), "+f"(d[96]), "+f"(d[97]), "+f"(d[98]), "+f"(d[99]), "+f"(d[100]), "+f"(d[101]), "+f"(d[102]), "+f"(d[103]), "+f"(d[104]), "+f"(d[105]), "+f"(d[106]), "+f"(d[107]), "+f"(d[108]), "+f"(d[109]), "+f"(d[110]), "+f"(d[111])
    : "l"(da), "l"(db), "r"(scale_d));
}
__device__ __forceinline__ void wgmma_n128_rs(float (&d)[64], uint32_t a0, uint32_t a1, uint32_t a2, uint32_t a3, uint64_t db, int scale_d) {
  asm volatile("{\n.reg .pred p;\nsetp.ne.b32 p, %69, 0;\n"
    "wgmma.mma_async.sync.aligned.m64n128k16.f32.bf16.bf16 {%0, %1, %2, %3, %4, %5, %6, %7, %8, %9, %10, %11, %12, %13, %14, %15, %16, %17, %18, %19, %20, %21, %22, %23, %24, %25, %26, %27, %28, %29, %30, %31, %32, %33, %34, %35, %36, %37, %38, %39, %40, %41, %42, %43, %44, %45, %46, %47, %48, %49, %50, %51, %52, %53, %54, %55, %56, %57, %58, %59, %60, %61, %62, %63}, {%64, %65, %66, %67}, %68, p, 1, 1, 1;\n}\n"
    : "+f"(d[0]), "+f"(d[1]), "+f"(d[2]), "+f"(d[3]), "+f"(d[4]), "+f"(d[5]), "+f"(d[6]), "+f"(d[7]), "+f"(d[8]), "+f"(d[9]), "+f"(d[10]), "+f"(d[11]), "+f"(d[12]), "+f"(d[13]), "+f"(d[14]), "+f"(d[15]), "+f"(d[16]), "+f"(d[17]), "+f"(d[18]), "+f"(d[19]), "+f"(d[20]), "+f"(d[21]), "+f"(d[22]), "+f"(d[23]), "+f"(d[24]), "+f"(d[25]), "+f"(d[26]), "+f"(d[27]), "+f"(d[28]), "+f"(d[29]), "+f"(d[30]), "+f"(d[31]), "+f"(d[32]), "+f"(d[33]), "+f"(d[34]), "+f"(d[35]), "+f"(d[36]), "+f"(d[37]), "+f"(d[38]), "+f"(d[39]), "+f"(d[40]), "+f"(d[41]), "+f"(d[42]), "+f"(d[43]), "+f"(d[44]), "+f"(d[45]), "+f"(d[46]), "+f"(d[47]), "+f"(d[48]), "+f"(d[49]), "+f"(d[50]), "+f"(d[51]), "+f"(d[52]), "+f"(d[53]), "+f"(d[54]), "+f"(d[55]), "+f"(d[56]), "+f"(d[57]), "+f"(d[58]), "+f"(d[59]), "+f"(d[60]), "+f"(d[61]), "+f"(d[62]), "+f"(d[63])
    : "r"(a0), "r"(a1), "r"(a2), "r"(a3), "l"(db), "r"(scale_d));
}

__device__ __forceinline__ float2 cadd(float2 a, float2 b) { return make_float2(a.x + b.x, a.y + b.y); }
__device__ __forceinline__ float2 csub(float2 a, float2 b) { return make_float2(a.x - b.x, a.y - b.y); }
__device__ __forceinline__ float2 cmul(float2 a, float2 b) { return make_float2(a.x * b.x - a.y * b.y, a.x * b.y + a.y * b.x); }
__device__ __forceinline__ float2 cconj(float2 a) { return make_float2(a.x, -a.y); }

template <int DIR> __device__ __forceinline__ void dft4(float2& a0, float2& a1, float2& a2, float2& a3) {
  float2 t0 = cadd(a0, a2), t1 = csub(a0, a2), t2 = cadd(a1, a3), t3 = csub(a1, a3);
  float2 t3r = DIR < 0 ? make_float2(t3.y, -t3.x) : make_float2(-t3.y, t3.x);
  a0 = cadd(t0, t2); a2 = csub(t0, t2); a1 = cadd(t1, t3r); a3 = csub(t1, t3r);
}
template <int DIR> __device__ __forceinline__ float2 mulw(float2 v, float c, float s) {
  return DIR < 0 ? make_float2(v.x * c + v.y * s, v.y * c - v.x * s) : make_float2(v.x * c - v.y * s, v.y * c + v.x * s);
}
template <int DIR> __device__ __forceinline__ float2 muli(float2 v) {
  return DIR < 0 ? make_float2(v.y, -v.x) : make_float2(-v.y, v.x);
}
#define O16(k) (4 * ((k) & 3) + ((k) >> 2))
#define O8(k) (2 * ((k) & 3) + ((k) >> 2))
template <int DIR> __device__ __forceinline__ void dft16(float2 (&v)[16]) {
  constexpr float C1 = 0.92387953251128674f, S1 = 0.38268343236508977f, R = 0.70710678118654752f;
#pragma unroll
  for (int n2 = 0; n2 < 4; n2++) dft4<DIR>(v[n2], v[4 + n2], v[8 + n2], v[12 + n2]);
  v[5] = mulw<DIR>(v[5], C1, S1);
  v[6] = mulw<DIR>(v[6], R, R);
  v[7] = mulw<DIR>(v[7], S1, C1);
  v[9] = mulw<DIR>(v[9], R, R);
  v[10] = muli<DIR>(v[10]);
  v[11] = mulw<DIR>(v[11], -R, R);
  v[13] = mulw<DIR>(v[13], S1, C1);
  v[14] = mulw<DIR>(v[14], -R, R);
  v[15] = mulw<DIR>(v[15], -C1, -S1);
#pragma unroll
  for (int k1 = 0; k1 < 4; k1++) dft4<DIR>(v[4 * k1], v[4 * k1 + 1], v[4 * k1 + 2], v[4 * k1 + 3]);
}
template <int DIR> __device__ __forceinline__ void dft8(float2 (&v)[8]) {
  constexpr float R = 0.70710678118654752f;
  dft4<DIR>(v[0], v[2], v[4], v[6]);
  dft4<DIR>(v[1], v[3], v[5], v[7]);
  v[3] = mulw<DIR>(v[3], R, R);
  v[5] = muli<DIR>(v[5]);
  v[7] = mulw<DIR>(v[7], -R, R);
#pragma unroll
  for (int k1 = 0; k1 < 4; k1++) {
    float2 a = v[2 * k1], b = v[2 * k1 + 1];
    v[2 * k1] = cadd(a, b); v[2 * k1 + 1] = csub(a, b);
  }
}
template <int N> __device__ __forceinline__ float2 twcs(int m) {
  m &= (N - 1);
  if (m >= N / 2) m -= N;
  float s, c;
  __sincosf((float)m * (6.283185307179586f / N), &s, &c);
  return make_float2(c, s);
}

__device__ __forceinline__ void twiddle16(float2 (&v)[16], int m) {
  const float2 w1 = twcs<2048>(m);
  float2 w = w1;
#pragma unroll
  for (int k = 1; k < 16; k++) {
    v[O16(k)] = mulw<-1>(v[O16(k)], w.x, w.y);
    if (k < 15) w = cmul(w, w1);
  }
}
__device__ __forceinline__ float2* tile_at(uint8_t* tile, int k, int r) {
  return reinterpret_cast<float2*>(tile + k * 128 + ((((r >> 1) ^ k) & 7) << 4) + (r & 1) * 8);
}
constexpr int SPITCH = 260;

constexpr int STEP = 45056;
constexpr int W1_STAGE = 14336;
constexpr int SM_FFT = 184 * 1024;
constexpr int SM_WT = SM_FFT + 32768;
constexpr int SM_BAR = SM_WT + 8192;
constexpr int SM_TAB = SM_BAR + 256;
constexpr int SM_TOTAL = SM_TAB + 1280;
constexpr int NTHREADS = 384;

__device__ __forceinline__ float gelu2(float x) {
  float u = x * (0.7978845608028654f + 0.035677408136300125f * x * x);
  float th;
  asm("tanh.approx.f32 %0, %1;" : "=f"(th) : "f"(u));
  return fmaf(x, th, x);
}
__device__ __forceinline__ unsigned grid_arrive(unsigned* cnt) {
  __threadfence();
  unsigned old = atomicAdd(cnt, 1u);
  return (old / 129u + 1u) * 129u;
}
__device__ __forceinline__ void grid_wait(const unsigned* cnt, unsigned target) {
  int it = 0;
  while ((int)(ld_acquire(cnt) - target) < 0) {
    if (++it > (1 << 22)) __trap();
  }
}
__device__ __forceinline__ uint32_t piece_off(int p) {
  if (p >= 12) p -= 12;
  const int s = (p * 11) >> 5;
  return (uint32_t)(s * STEP + (p - 3 * s) * W1_STAGE);
}

struct Maps { CUtensorMap x, w1, w2, spec, wt; };

__device__ __forceinline__ void issue_items(const uint8_t* smem, int first, int n) {
#pragma unroll 1
  for (int i = first; i < first + n; i++) {
    const uint4 a = *reinterpret_cast<const uint4*>(smem + SM_TAB + i * 32);
    const uint4 c = *reinterpret_cast<const uint4*>(smem + SM_TAB + i * 32 + 16);
    if (c.w) mbar_expect_tx(a.w, c.w);
    tma_load_3d(a.z, reinterpret_cast<const CUtensorMap*>((uint64_t)a.x | ((uint64_t)a.y << 32)), (int)c.x, (int)c.y, (int)c.z, a.w);
  }
}

__device__ __forceinline__ void gemm_part(uint8_t* smem, const Maps& maps, const __nv_bfloat16* __restrict__ b1, int rt, int sp) {
  const uint32_t sb = smem_u32(smem);
  const int tid = threadIdx.x, warp = tid >> 5, lane = tid & 31, wg = warp >> 2;
  const uint32_t bar_full1 = sb + SM_BAR, bar_full2 = sb + SM_BAR + 64;
  unsigned* relcnt = reinterpret_cast<unsigned*>(smem + SM_BAR + 128);
  const uint32_t bar_stats = sb + SM_BAR + 160, bar_st = sb + SM_BAR + 224;
  uint32_t ha[56];
      auto release = [&](int j) {
        __syncwarp();
        if (lane == 0) {
          __threadfence_block();
          if ((atomicAdd(&relcnt[j & 3], 1u) & 7u) == 7u) {
            __threadfence_block();
            issue_items(smem, 3 * j + 12, 3);
          }
        }
      };
      {
        float acc[112];
#pragma unroll
        for (int i = 0; i < 112; i++) acc[i] = 0.f;
        float2 st0 = make_float2(0.f, 0.f), st1 = st0;
        const uint64_t dA = make_desc(sb + __shfl_sync(0xffffffffu, wg, 0) * 8192, 16, 1024, 1), dB = make_desc(sb + 16384, 2048, 512, 2);
#pragma unroll 1
        for (int j = 0; j < 8; j++) {
          const uint32_t base = (j & 3) * STEP;
          mbar_wait(bar_full1 + 8 * (j & 3), j >> 2);
          if (tid == 0 && j == 0) TS(24);
          wgmma_fence();
#pragma unroll
          for (int kk = 0; kk < 4; kk++)
            wgmma_n224_ss(acc, dA + ((base + kk * 32) >> 4), dB + ((base + (kk >> 1) * W1_STAGE + (kk & 1) * 1024) >> 4), 1);
          wgmma_commit();
          if (j == 6) {
        mbar_wait(bar_stats, 0);
        if (tid < 224) {
          float c0 = 0.f, c1 = 0.f;
          const float2* pc = g_cs + (sp * 32 + (tid & 1) * 16) * 112 + (tid >> 1);
#pragma unroll
          for (int i = 0; i < 16; i++) { const float2 c = __ldcg(pc + i * 112); c0 += c.x; c1 += c.y; }
          c0 += __shfl_xor_sync(0xffffffffu, c0, 1); c1 += __shfl_xor_sync(0xffffffffu, c1, 1);
          const uint32_t bw = __ldg(reinterpret_cast<const uint32_t*>(b1 + sp * FC) + (tid >> 1));
          reinterpret_cast<float4*>(smem + SM_WT)[tid >> 1] = make_float4(c0, c1, bflo(bw), bfhi(bw));
        }
        const int row = rt * 128 + warp * 16 + (lane >> 2);
        st0 = __ldcg(&g_stats[row]); st1 = __ldcg(&g_stats[row + 8]);
          }
          if (j > 0) {
            wgmma_wait<1>();
            release(j - 1);
          }
        }
        wgmma_wait<0>();
        if (tid == 0) TS(2);
        named_bar(1, 256);
        if (tid == 0) {
          issue_items(smem, 33, 3);
        }
        const float4* csb = reinterpret_cast<const float4*>(smem + SM_WT) + (lane & 3);
#pragma unroll
        for (int j = 0; j < 28; j++) {
          const float4 c = csb[j * 4];
          ha[2 * j] = pack_bf16(gelu2(fmaf(fmaf(-st0.x, c.x, acc[4 * j]), st0.y, c.z)), gelu2(fmaf(fmaf(-st0.x, c.y, acc[4 * j + 1]), st0.y, c.w)));
          ha[2 * j + 1] = pack_bf16(gelu2(fmaf(fmaf(-st1.x, c.x, acc[4 * j + 2]), st1.y, c.z)), gelu2(fmaf(fmaf(-st1.x, c.y, acc[4 * j + 3]), st1.y, c.w)));
        }
      }
      if (tid == 0) TS(4);
      if (wg == 1) named_bar(2, 256);
#pragma unroll 1
      for (int jq = 0; jq < NJOB; jq++) {
        float acc[64];
#pragma unroll
        for (int h = 0; h < 2; h++) {
          const uint32_t o0 = piece_off(4 * jq + 2 * h), o1 = piece_off(4 * jq + 2 * h + 1);
          const uint64_t dW = make_desc(sb + o0, o1 - o0, 1024, 1);
          mbar_wait(bar_full2 + 8 * (2 * jq + h), 0);
          wgmma_fence();
#pragma unroll
          for (int kk = 0; kk < 7; kk++) {
            const int kb = h * 7 + kk;
            wgmma_n128_rs(acc, ha[4 * kb], ha[4 * kb + 1], ha[4 * kb + 2], ha[4 * kb + 3], dW + kk * 128, kb > 0);
          }
          wgmma_commit();
        }
        if (jq == 0 && wg == 0) asm volatile("bar.arrive 2, 256;" ::: "memory");
        wgmma_wait<0>();
        if (jq == 0 && lane == 0) {
          __threadfence_block();
          if (atomicAdd(&relcnt[4], 1u) == 7u) {
            __threadfence_block();
            issue_items(smem, 36, 4);
          }
        }
        uint4* dstp = g_part + ((((size_t)rt * NJOB + jq) * 8 + warp) * 8 + sp) * 256 + lane;
#pragma unroll
        for (int i = 0; i < 8; i++)
          dstp[i * 32] = make_uint4(pack_bf16(acc[8 * i], acc[8 * i + 1]), pack_bf16(acc[8 * i + 2], acc[8 * i + 3]),
                                    pack_bf16(acc[8 * i + 4], acc[8 * i + 5]), pack_bf16(acc[8 * i + 6], acc[8 * i + 7]));
        __syncwarp();
        if (lane == 0) mbar_arrive(bar_st + 8 * jq);
        if (tid == 0 && jq == 3) TS(8);
      }
}

__global__ void __launch_bounds__(NTHREADS, 1)
k_mega(const __nv_bfloat16* __restrict__ x, const __nv_bfloat16* __restrict__ wr, const __nv_bfloat16* __restrict__ wi,
       const __nv_bfloat16* __restrict__ w1, const __nv_bfloat16* __restrict__ b1, const __nv_bfloat16* __restrict__ b2, __nv_bfloat16* __restrict__ out,
       const __grid_constant__ Maps maps) {
  extern __shared__ __align__(1024) uint8_t smem[];
  const uint32_t sb = smem_u32(smem);
  const int rt = blockIdx.x >> 3, sp = blockIdx.x & 7;
  const int warp = threadIdx.x >> 5, lane = threadIdx.x & 31;
  const int s0 = blockIdx.x * 16;
  if (threadIdx.x == 0) TS(0);
  const uint32_t bar_full1 = sb + SM_BAR;
  const uint32_t bar_full2 = sb + SM_BAR + 64;
  unsigned* relcnt = reinterpret_cast<unsigned*>(smem + SM_BAR + 128);
  const uint32_t bar_stats = sb + SM_BAR + 160;
  const uint32_t bar_p1 = sb + SM_BAR + 168;
  const uint32_t bar_tile = sb + SM_BAR + 176;
  const uint32_t bar_st = sb + SM_BAR + 224;
  const uint32_t bar_g = sb + SM_BAR + 192;
  uint8_t* tile = smem + SM_FFT;

  if (threadIdx.x == 0) {
    for (int i = 0; i < 4; i++) mbar_init(bar_full1 + 8 * i, 1);
    for (int i = 0; i < 8; i++) mbar_init(bar_full2 + 8 * i, 2);
    mbar_init(bar_stats, 1); mbar_init(bar_p1, 256); mbar_init(bar_tile, 1);
    for (int i = 0; i < 4; i++) { mbar_init(bar_g + 8 * i, 1); mbar_init(bar_st + 8 * i, 8); }
    for (int i = 0; i < 5; i++) relcnt[i] = 0;
    asm volatile("fence.mbarrier_init.release.cluster;" ::: "memory");
  }
  if (warp == 1) {
#pragma unroll 1
    for (int i = lane; i < 40; i += 32) {
      uint64_t mp; uint32_t dst, bar, bytes; int c0, c1, c2;
      if (i < 24) {
        const int j = (i * 11) >> 5, part = i - 3 * j;
        bar = bar_full1 + 8 * (j & 3);
        bytes = part ? 0 : STEP;
        dst = sb + (j & 3) * STEP + (part ? 16384 + (part - 1) * W1_STAGE : 0);
        mp = (uint64_t)(part ? &maps.w1 : &maps.x);
        c0 = part ? 0 : j * 64; c1 = part ? j * 64 + (part - 1) * 32 : rt * 128; c2 = part ? sp * 7 : 0;
      } else {
        const int p = i - 24;
        bar = bar_full2 + 8 * (p >> 1);
        bytes = W1_STAGE;
        dst = sb + piece_off(p);
        mp = (uint64_t)&maps.w2;
        c0 = (p >> 2) * 128 + (p & 1) * 64; c1 = sp * FC + ((p >> 1) & 1) * 112; c2 = 0;
      }
      *reinterpret_cast<uint4*>(smem + SM_TAB + i * 32) = make_uint4((uint32_t)mp, (uint32_t)(mp >> 32), dst, bar);
      *reinterpret_cast<uint4*>(smem + SM_TAB + i * 32 + 16) = make_uint4(c0, c1, c2, bytes);
    }
  }
  __syncthreads();
  if (threadIdx.x == 32 && blockIdx.x < 128) issue_items(smem, 0, 12);

  if (warp >= 8) {
    const int t = threadIdx.x & 127;
    const bool extra = blockIdx.x == 128;
    if (!extra) {
      const uint32_t stg = (uint32_t)(SM_WT + (warp - 8) * 2048);
      if (t < 16) {
        const size_t o = (size_t)(s0 + t) * DF_ + 256;
        g_wt[(size_t)256 * S_ + s0 + t] = (uint32_t)__ldg(reinterpret_cast<const unsigned short*>(wr) + o) |
                                          ((uint32_t)__ldg(reinterpret_cast<const unsigned short*>(wi) + o) << 16);
      }
      uint32_t wv[2][16];
      {
        const unsigned short* pr = reinterpret_cast<const unsigned short*>(wr) + (size_t)s0 * DF_ + t;
        const unsigned short* pi = reinterpret_cast<const unsigned short*>(wi) + (size_t)s0 * DF_ + t;
#pragma unroll
        for (int u = 0; u < 32; u++)
          wv[u >> 4][u & 15] = (uint32_t)__ldg(pr + (u & 15) * DF_ + (u >> 4) * 128) | ((uint32_t)__ldg(pi + (u & 15) * DF_ + (u >> 4) * 128) << 16);
      }
#pragma unroll
      for (int rd = 0; rd < 2; rd++) {
        if (rd && lane == 0) asm volatile("cp.async.bulk.wait_group.read 0;" ::: "memory");
        __syncwarp();
#pragma unroll
        for (int c = 0; c < 4; c++)
          *reinterpret_cast<uint4*>(smem + stg + lane * 64 + ((c ^ ((lane >> 1) & 3)) << 4)) =
              make_uint4(wv[rd][4 * c], wv[rd][4 * c + 1], wv[rd][4 * c + 2], wv[rd][4 * c + 3]);
        fence_async();
        __syncwarp();
        if (lane == 0) {
          tma_store_2d(&maps.wt, s0, rd * 128 + (warp - 8) * 32, sb + stg);
          asm volatile("cp.async.bulk.commit_group;" ::: "memory");
        }
      }
      if (lane == 0) { asm volatile("cp.async.bulk.wait_group 0;" ::: "memory"); __threadfence(); }
    }
    named_bar(3, 128);
    if (t == 0) {
      if (!extra) {
        mbar_wait(bar_p1, 0);
        tma_store_2d(&maps.spec, s0, 0, sb + SM_FFT);
        tma_store_commit_wait();
      }
      const unsigned target = grid_arrive(&g_bar[0]);
      grid_wait(&g_bar[0], target);
      mbar_arrive(bar_stats);
    }
    named_bar(3, 128);
    if (t == 0) TS(13);
    {
      float2* buf = reinterpret_cast<float2*>(tile);
      const int k1 = t >> 3, m2 = t & 7;
      const int c0 = extra ? 256 : blockIdx.x * 2, nc = extra ? 1 : 2;
      float2 vn[16];
      uint32_t wn[16];
#pragma unroll 1
      for (int c = -1; c < nc; c++) {
        uint32_t wq[16];
        if (c >= 0) {
#pragma unroll
          for (int i = 0; i < 16; i++) { buf[128 * i + t] = vn[i]; wq[i] = wn[i]; }
        }
        if (c + 1 < nc) {
#pragma unroll
          for (int i = 0; i < 16; i++) {
            vn[i] = __ldcg(g_spec + (size_t)(c0 + c + 1) * S_ + 128 * i + t);
            wn[i] = __ldcg(g_wt + (size_t)(c0 + c + 1) * S_ + 128 * i + t);
          }
        }
        if (c < 0) continue;
#pragma unroll 1
        for (int it = 0; it < 2; it++) {
#pragma unroll 1
          for (int p = 0; p < 2; p++) {
            const float2* in = buf + (p ? k1 * 136 + m2 : t);
            const int is = p ? 8 : 128;
            float2 v[16];
#pragma unroll
            for (int i = 0; i < 16; i++) v[i] = in[i * is];
            dft16<-1>(v);
            twiddle16(v, p ? 16 * m2 : t);
            named_bar(3, 128);
            float2* o = buf + (p ? k1 * 9 + m2 : t);
            const int os = p ? 144 : 136;
#pragma unroll
            for (int kk = 0; kk < 16; kk++) o[kk * os] = v[O16(kk)];
            named_bar(3, 128);
          }
          float2 e[2][8];
#pragma unroll
          for (int m = 0; m < 8; m++) { e[0][m] = buf[t * 9 + m]; e[1][m] = buf[(t + 128) * 9 + m]; }
          dft8<-1>(e[0]);
          dft8<-1>(e[1]);
          named_bar(3, 128);
          if (it == 0) {
            constexpr float SC = 1.0f / (2048.0f * 512.0f);
#pragma unroll
            for (int i = 0; i < 16; i++)
              buf[128 * i + t] = cconj(cmul(e[i & 1][O8(i >> 1)], make_float2(bflo(wq[i]) * SC, bfhi(wq[i]) * SC)));
          } else {
            float2* col = g_spec + (size_t)(c0 + c) * S_ + t;
#pragma unroll
            for (int i = 0; i < 16; i++) col[128 * i] = cconj(e[i & 1][O8(i >> 1)]);
          }
        }
      }
    }
    named_bar(3, 128);
    if (warp == 9 && lane < 8 && !extra) {
#pragma unroll 1
      for (int jq = 0; jq < NJOB; jq++) {
        mbar_wait(bar_st + 8 * jq, 0);
        __threadfence();
        atomicAdd(&g_flag[(rt * NJOB + jq) * 8 + lane], 1u);
      }
    }
    if (t == 64 && !extra) {
        mbar_wait(bar_st + 24, 0);
#pragma unroll 1
        for (int jq = 0; jq < NJOB; jq++) {
          unsigned* fl = &g_flag[(rt * NJOB + jq) * 8 + sp];
          int it = 0;
          while (ld_acquire(fl) < 8u) {
            if (++it > (1 << 22)) __trap();
          }
          *fl = 0u;
          fence_async();
          mbar_expect_tx(bar_g + 8 * jq, jq ? 32768 : 32768 + 17 * 1024);
          asm volatile("cp.async.bulk.shared::cluster.global.mbarrier::complete_tx::bytes [%0], [%1], %2, [%3];"
                       ::"r"(sb + jq * 32768), "l"(g_part + (((size_t)rt * NJOB + jq) * 8 + sp) * 8 * 256), "r"(32768), "r"(bar_g + 8 * jq) : "memory");
          if (jq == 0) {
#pragma unroll 1
            for (int i = 0; i < 17; i++)
              asm volatile("cp.async.bulk.shared::cluster.global.mbarrier::complete_tx::bytes [%0], [%1], %2, [%3];"
                           ::"r"(sb + 131072 + i * SPITCH * 4), "l"(i < 16 ? x + (size_t)(s0 + i) * D_ : b2), "r"(1024), "r"(bar_g) : "memory");
          }
        }
    }
    if (t == 0) {
      TS(14);
      const unsigned target = grid_arrive(&g_bar[1]);
      if (!extra) {
        grid_wait(&g_bar[1], target);
        TS(15);
        fence_async();
        mbar_expect_tx(bar_tile, 32768);
        tma_load_2d(sb + SM_FFT, &maps.spec, s0, 0, bar_tile);
      }
    }
  } else {
    if (blockIdx.x == 128) return;
    const int tid = threadIdx.x;
    const int r = tid & 15, q = tid >> 4;
#pragma unroll 1
    for (int ph = 0; ph < 3; ph++) {
      if (ph) {
        float y256 = 0.f;
        if (ph == 2) {
          mbar_wait(bar_tile, 0);
          y256 = __ldcg(&g_spec[(size_t)256 * S_ + s0 + r]).x;
        }
        const float sg = ph == 1 ? -1.f : 1.f, sc = ph == 1 ? 0.5f : 1.f;
        float2 tw = twcs<512>(q);
#pragma unroll 2
        for (int i = 0; i < 8; i++) {
          const int j = q + 16 * i;
          float2* pa = tile_at(tile, j, r);
          float2* pb = tile_at(tile, j == 0 ? 128 : 256 - j, r);
          const float2 A = *pa, B = *pb;
          const float2 P = make_float2(sc * (A.x + B.x), sc * (A.y - B.y)), M = make_float2(sc * (A.x - B.x), sc * (A.y + B.y));
          const float ts = sg * tw.y;
          const float2 T = make_float2(M.x * tw.x - M.y * ts, M.y * tw.x + M.x * ts);
          tw = cmul(tw, make_float2(0.98078528040323044f, 0.19509032201612825f));
          const float2 V = make_float2(-sg * T.y, sg * T.x);
          if (j) {
            *pa = make_float2(P.x + V.x, -sg * (P.y + V.y));
            *pb = make_float2(P.x - V.x, sg * (P.y - V.y));
          } else if (ph == 1) {
            g_spec[(size_t)256 * S_ + s0 + r] = make_float2(A.x - A.y, 0.f);
            *pa = make_float2(A.x + A.y, 0.f);
            *pb = cconj(B);
          } else {
            *pa = make_float2(A.x + y256, y256 - A.x);
            *pb = make_float2(2.f * B.x, 2.f * B.y);
          }
        }
      }
      if (ph == 1) {
        fence_async();
        mbar_arrive(bar_p1);
        gemm_part(smem, maps, b1, rt, sp);
        continue;
      }
      if (ph == 0) {
        uint32_t w[16];
        const uint32_t* xw = reinterpret_cast<const uint32_t*>(x + (size_t)(s0 + q) * D_);
#pragma unroll
        for (int n1 = 0; n1 < 16; n1++) w[n1] = __ldg(xw + 16 * n1 + r);
        if ((tid & 127) < 112) {
          const uint32_t* pw = reinterpret_cast<const uint32_t*>(w1 + (size_t)(rt * 32 + (tid >> 7) * 16) * F_ + sp * FC) + (tid & 127);
          float c0 = 0.f, c1 = 0.f;
#pragma unroll
          for (int k = 0; k < 16; k++) { const uint32_t ww = __ldg(pw + k * (F_ / 2)); c0 += bflo(ww); c1 += bfhi(ww); }
          g_cs[(sp * 32 + rt * 2 + (tid >> 7)) * 112 + (tid & 127)] = make_float2(c0, c1);
        }
        float sum = 0.f;
#pragma unroll
        for (int n1 = 0; n1 < 16; n1++) sum += bflo(w[n1]) + bfhi(w[n1]);
#pragma unroll
        for (int o = 1; o < 16; o <<= 1) sum += __shfl_xor_sync(0xffffffffu, sum, o);
        const float mean = sum * (1.0f / D_);
        float sq = 0.f;
#pragma unroll
        for (int n1 = 0; n1 < 16; n1++) {
          float a = bflo(w[n1]) - mean, c = bfhi(w[n1]) - mean;
          sq += a * a + c * c;
        }
#pragma unroll
        for (int o = 1; o < 16; o <<= 1) sq += __shfl_xor_sync(0xffffffffu, sq, o);
        const uint32_t nm2 = pack_bf16(-mean, -mean);
        float sd, rs;
        asm("sqrt.approx.f32 %0, %1;" : "=f"(sd) : "f"(bf16r(bf16r(sq * (1.0f / D_)) + 1e-5f)));
        asm("rcp.approx.f32 %0, %1;" : "=f"(rs) : "f"(bf16r(sd)));
        if (r == 0) g_stats[s0 + q] = make_float2(-bflo(nm2), rs);
#pragma unroll
        for (int n1 = 0; n1 < 16; n1++) {
          const uint32_t d = hadd2_bf16(w[n1], nm2);
          const uint32_t xn = pack_bf16(bflo(d) * rs, bfhi(d) * rs);
          *tile_at(tile, 16 * n1 + r, q) = make_float2(bflo(xn), bfhi(xn));
        }
      }
      named_bar(1, 256);
      {
        uint8_t* pa = reinterpret_cast<uint8_t*>(tile_at(tile, q, r));
        const uint8_t* pb = tile + q * 2048 + (r & 1) * 8;
#pragma unroll 1
        for (int p = 0; p < 2; p++) {
          float2 v[16];
#pragma unroll
          for (int i = 0; i < 16; i++)
            v[i] = *reinterpret_cast<const float2*>(p ? pb + i * 128 + ((((r >> 1) ^ i) & 7) << 4) : pa + i * 2048);
          dft16<-1>(v);
          if (p == 0) twiddle16(v, 8 * q);
          named_bar(1, 256);
          if (p && ph) {
#pragma unroll
            for (int i = 0; i < 16; i++) reinterpret_cast<uint32_t*>(tile)[r * SPITCH + q + 16 * i] = pack_bf16(v[O16(i)].x, -v[O16(i)].y);
          } else {
#pragma unroll
            for (int i = 0; i < 16; i++) *reinterpret_cast<float2*>(pa + i * 2048) = v[O16(i)];
          }
          named_bar(1, 256);
        }
      }
    }
    if (tid == 0) TS(16);
    {
      const int g = lane >> 2;
      const uint32_t* stile = reinterpret_cast<const uint32_t*>(tile);
      const uint32_t* xs = reinterpret_cast<const uint32_t*>(smem + 131072);
#pragma unroll 1
      for (int jq = 0; jq < NJOB; jq++) {
        const int cw = jq * 64 + 8 * warp + (lane & 3);
        mbar_wait(bar_g + 8 * jq, 0);
        if (tid == 0) TS(17 + jq);
        const uint4* src = reinterpret_cast<const uint4*>(smem + jq * 32768) + tid;
        float o[8];
#pragma unroll
        for (int c = 0; c < 8; c++) o[c] = 0.f;
#pragma unroll
        for (int s = 0; s < 8; s++) {
          const uint4 v = src[s * 256];
          o[0] += bflo(v.x); o[1] += bfhi(v.x); o[2] += bflo(v.y); o[3] += bfhi(v.y);
          o[4] += bflo(v.z); o[5] += bfhi(v.z); o[6] += bflo(v.w); o[7] += bfhi(v.w);
        }
#pragma unroll
        for (int c = 0; c < 4; c++) {
          const int row = g + 8 * (c & 1), w = cw + 4 * (c >> 1);
          const uint32_t sw = stile[row * SPITCH + w];
          const uint32_t p = hadd2_bf16(pack_bf16(0.5f * o[2 * c], 0.5f * o[2 * c + 1]), xs[16 * SPITCH + w]);
          const float oa = bflo(p), ob = bfhi(p);
          const uint32_t gg = pack_bf16(__fdividef(oa, 1.0f + __expf(-oa)), __fdividef(ob, 1.0f + __expf(-ob)));
          const uint32_t sg = pack_bf16(bflo(sw) * bflo(gg), bfhi(sw) * bfhi(gg));
          reinterpret_cast<uint32_t*>(out)[(size_t)(s0 + row) * 256 + w] = hadd2_bf16(xs[row * SPITCH + w], sg);
        }
        if (tid == 0 && jq == 3) TS(23);
      }
    }
  }
}

typedef CUresult (*EncodeFn)(CUtensorMap*, CUtensorMapDataType, cuuint32_t, void*, const cuuint64_t*, const cuuint64_t*,
                             const cuuint32_t*, const cuuint32_t*, CUtensorMapInterleave, CUtensorMapSwizzle,
                             CUtensorMapL2promotion, CUtensorMapFloatOOBfill);

}

extern "C" void kernel_launch(void* const* d_in, const int* in_sizes, int n_in, void* d_out, int out_size) {
  const __nv_bfloat16* x = (const __nv_bfloat16*)d_in[0];
  const __nv_bfloat16* wr = (const __nv_bfloat16*)d_in[1];
  const __nv_bfloat16* wi = (const __nv_bfloat16*)d_in[2];
  const __nv_bfloat16* w1 = (const __nv_bfloat16*)d_in[4];
  const __nv_bfloat16* b1 = (const __nv_bfloat16*)d_in[5];
  const __nv_bfloat16* w2 = (const __nv_bfloat16*)d_in[6];
  const __nv_bfloat16* b2 = (const __nv_bfloat16*)d_in[7];
  __nv_bfloat16* out = (__nv_bfloat16*)d_out;

  static EncodeFn enc = nullptr;
  static void* p_spec = nullptr;
  static void* p_wt = nullptr;
  if (!enc) {
    void* fn = nullptr;
    cudaDriverEntryPointQueryResult qr;
    cudaGetDriverEntryPoint("cuTensorMapEncodeTiled", &fn, cudaEnableDefault, &qr);
    enc = (EncodeFn)fn;
    cudaFuncSetAttribute(k_mega, cudaFuncAttributeMaxDynamicSharedMemorySize, SM_TOTAL);
    cudaGetSymbolAddress(&p_spec, g_spec);
    cudaGetSymbolAddress(&p_wt, g_wt);
  }
  Maps m;
  const cuuint32_t es[3] = {1, 1, 1};
  {
    cuuint64_t dims[3] = {(cuuint64_t)D_, (cuuint64_t)S_, 1};
    cuuint64_t strides[2] = {(cuuint64_t)D_ * 2, (cuuint64_t)D_ * 2 * S_};
    cuuint32_t box[3] = {64, 128, 1};
    enc(&m.x, CU_TENSOR_MAP_DATA_TYPE_BFLOAT16, 3, (void*)x, dims, strides, box, es, CU_TENSOR_MAP_INTERLEAVE_NONE,
        CU_TENSOR_MAP_SWIZZLE_128B, CU_TENSOR_MAP_L2_PROMOTION_L2_128B, CU_TENSOR_MAP_FLOAT_OOB_FILL_NONE);
  }
  {
    cuuint64_t dims[3] = {32, 512, 56};
    cuuint64_t strides[2] = {(cuuint64_t)F_ * 2, 64};
    cuuint32_t box[3] = {32, 32, 7};
    enc(&m.w1, CU_TENSOR_MAP_DATA_TYPE_BFLOAT16, 3, (void*)w1, dims, strides, box, es, CU_TENSOR_MAP_INTERLEAVE_NONE,
        CU_TENSOR_MAP_SWIZZLE_64B, CU_TENSOR_MAP_L2_PROMOTION_L2_128B, CU_TENSOR_MAP_FLOAT_OOB_FILL_NONE);
  }
  {
    cuuint64_t dims[3] = {(cuuint64_t)D_, (cuuint64_t)F_, 1};
    cuuint64_t strides[2] = {(cuuint64_t)D_ * 2, (cuuint64_t)D_ * 2 * F_};
    cuuint32_t box[3] = {64, 112, 1};
    enc(&m.w2, CU_TENSOR_MAP_DATA_TYPE_BFLOAT16, 3, (void*)w2, dims, strides, box, es, CU_TENSOR_MAP_INTERLEAVE_NONE,
        CU_TENSOR_MAP_SWIZZLE_128B, CU_TENSOR_MAP_L2_PROMOTION_L2_128B, CU_TENSOR_MAP_FLOAT_OOB_FILL_NONE);
  }
  {
    cuuint64_t dims[2] = {(cuuint64_t)S_, 256};
    cuuint64_t strides[1] = {(cuuint64_t)S_ * 8};
    cuuint32_t box[2] = {16, 256};
    enc(&m.spec, CU_TENSOR_MAP_DATA_TYPE_FLOAT64, 2, p_spec, dims, strides, box, es, CU_TENSOR_MAP_INTERLEAVE_NONE,
        CU_TENSOR_MAP_SWIZZLE_128B, CU_TENSOR_MAP_L2_PROMOTION_NONE, CU_TENSOR_MAP_FLOAT_OOB_FILL_NONE);
  }
  {
    cuuint64_t dims[2] = {(cuuint64_t)S_, 257};
    cuuint64_t strides[1] = {(cuuint64_t)S_ * 4};
    cuuint32_t box[2] = {16, 32};
    enc(&m.wt, CU_TENSOR_MAP_DATA_TYPE_UINT32, 2, p_wt, dims, strides, box, es, CU_TENSOR_MAP_INTERLEAVE_NONE,
        CU_TENSOR_MAP_SWIZZLE_64B, CU_TENSOR_MAP_L2_PROMOTION_NONE, CU_TENSOR_MAP_FLOAT_OOB_FILL_NONE);
  }
  k_mega<<<129, NTHREADS, SM_TOTAL>>>(x, wr, wi, w1, b1, b2, out, m);
}
```

```cpp
#include <cuda_runtime.h>
#include <cuda_bf16.h>
#include <cuda.h>
#include <stdint.h>

namespace {

constexpr int S_ = 2048, D_ = 512, F_ = 1792, DF_ = 257;
constexpr int FC = 224;
constexpr int NJOB = 4;

__device__ __align__(1024) float2 g_spec[257 * 2048];
__device__ __align__(1024) uint32_t g_wt[257 * 2048];
__device__ uint4 g_part[16 * NJOB * 8 * 8 * 256];
__device__ float2 g_cs[8 * 32 * 112];
__device__ float2 g_stats[2048];
__device__ unsigned g_bar[1];
#define TS(i)

__device__ __forceinline__ uint32_t smem_u32(const void* p) { return (uint32_t)__cvta_generic_to_shared(p); }
__device__ __forceinline__ float bf16r(float x) { return __bfloat162float(__float2bfloat16_rn(x)); }
__device__ __forceinline__ float bflo(uint32_t w) { return __uint_as_float(w << 16); }
__device__ __forceinline__ float bfhi(uint32_t w) { return __uint_as_float(w & 0xffff0000u); }
__device__ __forceinline__ uint32_t pack_bf16(float lo, float hi) {
  uint32_t r;
  asm("cvt.rn.bf16x2.f32 %0, %1, %2;" : "=r"(r) : "f"(hi), "f"(lo));
  return r;
}
__device__ __forceinline__ uint32_t hadd2_bf16(uint32_t a, uint32_t b) {
  uint32_t r;
  asm("add.rn.bf16x2 %0, %1, %2;" : "=r"(r) : "r"(a), "r"(b));
  return r;
}
__device__ __forceinline__ void named_bar(int id, int n) { asm volatile("bar.sync %0, %1;" ::"r"(id), "r"(n) : "memory"); }
__device__ __forceinline__ void fence_async() { asm volatile("fence.proxy.async;" ::: "memory"); }

__device__ __forceinline__ void mbar_init(uint32_t bar, int cnt) { asm volatile("mbarrier.init.shared::cta.b64 [%0], %1;" ::"r"(bar), "r"(cnt) : "memory"); }
__device__ __forceinline__ void mbar_expect_tx(uint32_t bar, uint32_t bytes) { asm volatile("mbarrier.arrive.expect_tx.shared::cta.b64 _, [%0], %1;" ::"r"(bar), "r"(bytes) : "memory"); }
__device__ __forceinline__ void mbar_arrive(uint32_t bar) { asm volatile("mbarrier.arrive.shared::cta.b64 _, [%0];" ::"r"(bar) : "memory"); }
__device__ __forceinline__ void mbar_wait(uint32_t bar, uint32_t parity) {
  asm volatile(
      "{\n.reg .pred p, q;\n.reg .u32 c;\nmov.u32 c, 0;\n"
      "MW_L%=:\nmbarrier.try_wait.parity.shared::cta.b64 p, [%0], %1, %2;\n@p bra MW_D%=;\n"
      "add.u32 c, c, 1;\nsetp.lt.u32 q, c, 131072;\n@q bra MW_L%=;\ntrap;\nMW_D%=:\n}\n"
      ::"r"(bar), "r"(parity), "r"(20000u) : "memory");
}
__device__ __forceinline__ void tma_load_3d(uint32_t dst, const CUtensorMap* map, int c0, int c1, int c2, uint32_t bar) {
  asm volatile("cp.async.bulk.tensor.3d.shared::cluster.global.mbarrier::complete_tx::bytes [%0], [%1, {%3, %4, %5}], [%2];"
               ::"r"(dst), "l"((uint64_t)map), "r"(bar), "r"(c0), "r"(c1), "r"(c2) : "memory");
}
__device__ __forceinline__ void tma_load_2d(uint32_t dst, const CUtensorMap* map, int c0, int c1, uint32_t bar) {
  asm volatile("cp.async.bulk.tensor.2d.shared::cluster.global.mbarrier::complete_tx::bytes [%0], [%1, {%3, %4}], [%2];"
               ::"r"(dst), "l"((uint64_t)map), "r"(bar), "r"(c0), "r"(c1) : "memory");
}
__device__ __forceinline__ void tma_store_2d(const CUtensorMap* map, int c0, int c1, uint32_t src) {
  asm volatile("cp.async.bulk.tensor.2d.global.shared::cta.bulk_group [%0, {%2, %3}], [%1];"
               ::"l"((uint64_t)map), "r"(src), "r"(c0), "r"(c1) : "memory");
}
__device__ __forceinline__ void tma_store_commit_wait() {
  asm volatile("cp.async.bulk.commit_group;" ::: "memory");
  asm volatile("cp.async.bulk.wait_group 0;" ::: "memory");
}
__device__ __forceinline__ void wgmma_fence() { asm volatile("wgmma.fence.sync.aligned;" ::: "memory"); }
__device__ __forceinline__ void wgmma_commit() { asm volatile("wgmma.commit_group.sync.aligned;" ::: "memory"); }
template <int N> __device__ __forceinline__ void wgmma_wait() { asm volatile("wgmma.wait_group.sync.aligned %0;" ::"n"(N) : "memory"); }
__device__ __forceinline__ uint64_t make_desc(uint32_t addr, uint32_t lbo_bytes, uint32_t sbo_bytes, uint32_t swz) {
  uint64_t d = 0;
  d |= (uint64_t)((addr & 0x3FFFF) >> 4);
  d |= (uint64_t)((lbo_bytes & 0x3FFFF) >> 4) << 16;
  d |= (uint64_t)((sbo_bytes & 0x3FFFF) >> 4) << 32;
  d |= (uint64_t)swz << 62;
  return d;
}
__device__ __forceinline__ unsigned ld_acquire(const unsigned* p) {
  unsigned v;
  asm volatile("ld.acquire.gpu.global.u32 %0, [%1];" : "=r"(v) : "l"(p) : "memory");
  return v;
}

__device__ __forceinline__ void wgmma_n224_ss(float (&d)[112], uint64_t da, uint64_t db, int scale_d) {
  asm volatile("{\n.reg .pred p;\nsetp.ne.b32 p, %114, 0;\n"
    "wgmma.mma_async.sync.aligned.m64n224k16.f32.bf16.bf16 {%0, %1, %2, %3, %4, %5, %6, %7, %8, %9, %10, %11, %12, %13, %14, %15, %16, %17, %18, %19, %20, %21, %22, %23, %24, %25, %26, %27, %28, %29, %30, %31, %32, %33, %34, %35, %36, %37, %38, %39, %40, %41, %42, %43, %44, %45, %46, %47, %48, %49, %50, %51, %52, %53, %54, %55, %56, %57, %58, %59, %60, %61, %62, %63, %64, %65, %66, %67, %68, %69, %70, %71, %72, %73, %74, %75, %76, %77, %78, %79, %80, %81, %82, %83, %84, %85, %86, %87, %88, %89, %90, %91, %92, %93, %94, %95, %96, %97, %98, %99, %100, %101, %102, %103, %104, %105, %106, %107, %108, %109, %110, %111}, %112, %113, p, 1, 1, 0, 1;\n}\n"
    : "+f"(d[0]), "+f"(d[1]), "+f"(d[2]), "+f"(d[3]), "+f"(d[4]), "+f"(d[5]), "+f"(d[6]), "+f"(d[7]), "+f"(d[8]), "+f"(d[9]), "+f"(d[10]), "+f"(d[11]), "+f"(d[12]), "+f"(d[13]), "+f"(d[14]), "+f"(d[15]), "+f"(d[16]), "+f"(d[17]), "+f"(d[18]), "+f"(d[19]), "+f"(d[20]), "+f"(d[21]), "+f"(d[22]), "+f"(d[23]), "+f"(d[24]), "+f"(d[25]), "+f"(d[26]), "+f"(d[27]), "+f"(d[28]), "+f"(d[29]), "+f"(d[30]), "+f"(d[31]), "+f"(d[32]), "+f"(d[33]), "+f"(d[34]), "+f"(d[35]), "+f"(d[36]), "+f"(d[37]), "+f"(d[38]), "+f"(d[39]), "+f"(d[40]), "+f"(d[41]), "+f"(d[42]), "+f"(d[43]), "+f"(d[44]), "+f"(d[45]), "+f"(d[46]), "+f"(d[47]), "+f"(d[48]), "+f"(d[49]), "+f"(d[50]), "+f"(d[51]), "+f"(d[52]), "+f"(d[53]), "+f"(d[54]), "+f"(d[55]), "+f"(d[56]), "+f"(d[57]), "+f"(d[58]), "+f"(d[59]), "+f"(d[60]), "+f"(d[61]), "+f"(d[62]), "+f"(d[63]), "+f"(d[64]), "+f"(d[65]), "+f"(d[66]), "+f"(d[67]), "+f"(d[68]), "+f"(d[69]), "+f"(d[70]), "+f"(d[71]), "+f"(d[72]), "+f"(d[73]), "+f"(d[74]), "+f"(d[75]), "+f"(d[76]), "+f"(d[77]), "+f"(d[78]), "+f"(d[79]), "+f"(d[80]), "+f"(d[81]), "+f"(d[82]), "+f"(d[83]), "+f"(d[84]), "+f"(d[85]), "+f"(d[86]), "+f"(d[87]), "+f"(d[88]), "+f"(d[89]), "+f"(d[90]), "+f"(d[91]), "+f"(d[92]), "+f"(d[93]), "+f"(d[94]), "+f"(d[95]), "+f"(d[96]), "+f"(d[97]), "+f"(d[98]), "+f"(d[99]), "+f"(d[100]), "+f"(d[101]), "+f"(d[102]), "+f"(d[103]), "+f"(d[104]), "+f"(d[105]), "+f"(d[106]), "+f"(d[107]), "+f"(d[108]), "+f"(d[109]), "+f"(d[110]), "+f"(d[111])
    : "l"(da), "l"(db), "r"(scale_d));
}
__device__ __forceinline__ void wgmma_n128_rs(float (&d)[64], uint32_t a0, uint32_t a1, uint32_t a2, uint32_t a3, uint64_t db, int scale_d) {
  asm volatile("{\n.reg .pred p;\nsetp.ne.b32 p, %69, 0;\n"
    "wgmma.mma_async.sync.aligned.m64n128k16.f32.bf16.bf16 {%0, %1, %2, %3, %4, %5, %6, %7, %8, %9, %10, %11, %12, %13, %14, %15, %16, %17, %18, %19, %20, %21, %22, %23, %24, %25, %26, %27, %28, %29, %30, %31, %32, %33, %34, %35, %36, %37, %38, %39, %40, %41, %42, %43, %44, %45, %46, %47, %48, %49, %50, %51, %52, %53, %54, %55, %56, %57, %58, %59, %60, %61, %62, %63}, {%64, %65, %66, %67}, %68, p, 1, 1, 1;\n}\n"
    : "+f"(d[0]), "+f"(d[1]), "+f"(d[2]), "+f"(d[3]), "+f"(d[4]), "+f"(d[5]), "+f"(d[6]), "+f"(d[7]), "+f"(d[8]), "+f"(d[9]), "+f"(d[10]), "+f"(d[11]), "+f"(d[12]), "+f"(d[13]), "+f"(d[14]), "+f"(d[15]), "+f"(d[16]), "+f"(d[17]), "+f"(d[18]), "+f"(d[19]), "+f"(d[20]), "+f"(d[21]), "+f"(d[22]), "+f"(d[23]), "+f"(d[24]), "+f"(d[25]), "+f"(d[26]), "+f"(d[27]), "+f"(d[28]), "+f"(d[29]), "+f"(d[30]), "+f"(d[31]), "+f"(d[32]), "+f"(d[33]), "+f"(d[34]), "+f"(d[35]), "+f"(d[36]), "+f"(d[37]), "+f"(d[38]), "+f"(d[39]), "+f"(d[40]), "+f"(d[41]), "+f"(d[42]), "+f"(d[43]), "+f"(d[44]), "+f"(d[45]), "+f"(d[46]), "+f"(d[47]), "+f"(d[48]), "+f"(d[49]), "+f"(d[50]), "+f"(d[51]), "+f"(d[52]), "+f"(d[53]), "+f"(d[54]), "+f"(d[55]), "+f"(d[56]), "+f"(d[57]), "+f"(d[58]), "+f"(d[59]), "+f"(d[60]), "+f"(d[61]), "+f"(d[62]), "+f"(d[63])
    : "r"(a0), "r"(a1), "r"(a2), "r"(a3), "l"(db), "r"(scale_d));
}

__device__ __forceinline__ float2 cadd(float2 a, float2 b) { return make_float2(a.x + b.x, a.y + b.y); }
__device__ __forceinline__ float2 csub(float2 a, float2 b) { return make_float2(a.x - b.x, a.y - b.y); }
__device__ __forceinline__ float2 cmul(float2 a, float2 b) { return make_float2(a.x * b.x - a.y * b.y, a.x * b.y + a.y * b.x); }
__device__ __forceinline__ float2 cconj(float2 a) { return make_float2(a.x, -a.y); }

template <int DIR> __device__ __forceinline__ void dft4(float2& a0, float2& a1, float2& a2, float2& a3) {
  float2 t0 = cadd(a0, a2), t1 = csub(a0, a2), t2 = cadd(a1, a3), t3 = csub(a1, a3);
  float2 t3r = DIR < 0 ? make_float2(t3.y, -t3.x) : make_float2(-t3.y, t3.x);
  a0 = cadd(t0, t2); a2 = csub(t0, t2); a1 = cadd(t1, t3r); a3 = csub(t1, t3r);
}
template <int DIR> __device__ __forceinline__ float2 mulw(float2 v, float c, float s) {
  return DIR < 0 ? make_float2(v.x * c + v.y * s, v.y * c - v.x * s) : make_float2(v.x * c - v.y * s, v.y * c + v.x * s);
}
template <int DIR> __device__ __forceinline__ float2 muli(float2 v) {
  return DIR < 0 ? make_float2(v.y, -v.x) : make_float2(-v.y, v.x);
}
#define O16(k) (4 * ((k) & 3) + ((k) >> 2))
#define O8(k) (2 * ((k) & 3) + ((k) >> 2))
template <int DIR> __device__ __forceinline__ void dft16(float2 (&v)[16]) {
  constexpr float C1 = 0.92387953251128674f, S1 = 0.38268343236508977f, R = 0.70710678118654752f;
#pragma unroll
  for (int n2 = 0; n2 < 4; n2++) dft4<DIR>(v[n2], v[4 + n2], v[8 + n2], v[12 + n2]);
  v[5] = mulw<DIR>(v[5], C1, S1);
  v[6] = mulw<DIR>(v[6], R, R);
  v[7] = mulw<DIR>(v[7], S1, C1);
  v[9] = mulw<DIR>(v[9], R, R);
  v[10] = muli<DIR>(v[10]);
  v[11] = mulw<DIR>(v[11], -R, R);
  v[13] = mulw<DIR>(v[13], S1, C1);
  v[14] = mulw<DIR>(v[14], -R, R);
  v[15] = mulw<DIR>(v[15], -C1, -S1);
#pragma unroll
  for (int k1 = 0; k1 < 4; k1++) dft4<DIR>(v[4 * k1], v[4 * k1 + 1], v[4 * k1 + 2], v[4 * k1 + 3]);
}
template <int DIR> __device__ __forceinline__ void dft8(float2 (&v)[8]) {
  constexpr float R = 0.70710678118654752f;
  dft4<DIR>(v[0], v[2], v[4], v[6]);
  dft4<DIR>(v[1], v[3], v[5], v[7]);
  v[3] = mulw<DIR>(v[3], R, R);
  v[5] = muli<DIR>(v[5]);
  v[7] = mulw<DIR>(v[7], -R, R);
#pragma unroll
  for (int k1 = 0; k1 < 4; k1++) {
    float2 a = v[2 * k1], b = v[2 * k1 + 1];
    v[2 * k1] = cadd(a, b); v[2 * k1 + 1] = csub(a, b);
  }
}
template <int N> __device__ __forceinline__ float2 twcs(int m) {
  m &= (N - 1);
  if (m >= N / 2) m -= N;
  float s, c;
  __sincosf((float)m * (6.283185307179586f / N), &s, &c);
  return make_float2(c, s);
}

__device__ __forceinline__ void twiddle16(float2 (&v)[16], int m) {
  const float2 w1 = twcs<2048>(m), w2 = twcs<2048>(2 * m);
  float2 wo = w1, we = w2;
#pragma unroll
  for (int k = 1; k < 16; k += 2) {
    v[O16(k)] = mulw<-1>(v[O16(k)], wo.x, wo.y);
    if (k < 15) {
      v[O16(k + 1)] = mulw<-1>(v[O16(k + 1)], we.x, we.y);
      wo = cmul(wo, w2);
      if (k < 13) we = cmul(we, w2);
    }
  }
}
__device__ __forceinline__ float2* tile_at(uint8_t* tile, int k, int r) {
  return reinterpret_cast<float2*>(tile + k * 128 + ((((r >> 1) ^ k) & 7) << 4) + (r & 1) * 8);
}
constexpr int SPITCH = 260;

constexpr int STEP = 45056;
constexpr int W1_STAGE = 14336;
constexpr int SM_FFT = 184 * 1024;
constexpr int SM_WT = SM_FFT + 32768;
constexpr int SM_BAR = SM_WT + 8192;
constexpr int SM_TOTAL = SM_BAR + 256;
constexpr int NTHREADS = 384;

__device__ __forceinline__ float gelu2(float x) {
  float u = x * (0.7978845608028654f + 0.035677408136300125f * x * x);
  float th;
  asm("tanh.approx.f32 %0, %1;" : "=f"(th) : "f"(u));
  return fmaf(x, th, x);
}
__device__ __forceinline__ unsigned grid_arrive(unsigned* cnt) {
  __threadfence();
  unsigned old = atomicAdd(cnt, 1u);
  return (old / 129u + 1u) * 129u;
}
__device__ __forceinline__ void grid_wait(const unsigned* cnt, unsigned target) {
  int it = 0;
  while ((int)(ld_acquire(cnt) - target) < 0) {
    if (++it > (1 << 22)) __trap();
  }
}
__device__ __forceinline__ uint32_t piece_off(int p) {
  if (p >= 12) p -= 12;
  const int s = (p * 11) >> 5;
  return (uint32_t)(s * STEP + (p - 3 * s) * W1_STAGE);
}

struct Maps { CUtensorMap x, w1, w2, spec, wt; };

__device__ __forceinline__ void load_step(uint32_t sb, const Maps& maps, int rt, int sp, int j) {
  const uint32_t dst = sb + (j & 3) * STEP, bar = sb + SM_BAR + 8 * (j & 3);
  mbar_expect_tx(bar, STEP);
  tma_load_2d(dst, &maps.x, j * 64, rt * 128, bar);
  tma_load_3d(dst + 16384, &maps.w1, 0, j * 64, sp * 7, bar);
  tma_load_3d(dst + 16384 + W1_STAGE, &maps.w1, 0, j * 64 + 32, sp * 7, bar);
}
__device__ __forceinline__ void load_piece(uint32_t sb, const Maps& maps, int sp, int p) {
  const uint32_t bar = sb + SM_BAR + 64 + 8 * (p >> 1);
  mbar_expect_tx(bar, W1_STAGE);
  tma_load_2d(sb + piece_off(p), &maps.w2, (p >> 2) * 128 + (p & 1) * 64, sp * FC + ((p >> 1) & 1) * 112, bar);
}

__device__ __forceinline__ void gemm_part(uint8_t* smem, const Maps& maps, const __nv_bfloat16* __restrict__ b1, int rt, int sp) {
  const uint32_t sb = smem_u32(smem);
  const int tid = threadIdx.x, warp = tid >> 5, lane = tid & 31, wg = warp >> 2;
  const uint32_t bar_full1 = sb + SM_BAR, bar_full2 = sb + SM_BAR + 64;
  unsigned* relcnt = reinterpret_cast<unsigned*>(smem + SM_BAR + 128);
  const uint32_t bar_stats = sb + SM_BAR + 160;
  uint32_t ha[56];
      auto release = [&](int j) {
        __syncwarp();
        if (lane == 0) {
          __threadfence_block();
          if ((atomicAdd(&relcnt[j & 3], 1u) & 7u) == 7u) {
            __threadfence_block();
            if (j < 4) load_step(sb, maps, rt, sp, j + 4);
            else {
#pragma unroll 1
              for (int p = 3 * (j - 4); p < 3 * (j - 4) + 3; p++) load_piece(sb, maps, sp, p);
            }
          }
        }
      };
      {
        float acc[112];
#pragma unroll
        for (int i = 0; i < 112; i++) acc[i] = 0.f;
        const uint64_t dA = make_desc(sb + __shfl_sync(0xffffffffu, wg, 0) * 8192, 16, 1024, 1), dB = make_desc(sb + 16384, 2048, 512, 2);
#pragma unroll 1
        for (int j = 0; j < 8; j++) {
          const uint32_t base = (j & 3) * STEP;
          mbar_wait(bar_full1 + 8 * (j & 3), j >> 2);
          if (tid == 0 && j == 0) TS(24);
          wgmma_fence();
#pragma unroll
          for (int kk = 0; kk < 4; kk++)
            wgmma_n224_ss(acc, dA + ((base + kk * 32) >> 4), dB + ((base + (kk >> 1) * W1_STAGE + (kk & 1) * 1024) >> 4), 1);
          wgmma_commit();
          if (j > 0) {
            wgmma_wait<1>();
            release(j - 1);
          }
        }
        wgmma_wait<0>();
        if (tid == 0) TS(2);
        mbar_wait(bar_stats, 0);
        if (tid < 224) {
          float c0 = 0.f, c1 = 0.f;
          const float2* pc = g_cs + (sp * 32 + (tid & 1) * 16) * 112 + (tid >> 1);
#pragma unroll
          for (int i = 0; i < 16; i++) { const float2 c = __ldcg(pc + i * 112); c0 += c.x; c1 += c.y; }
          c0 += __shfl_xor_sync(0xffffffffu, c0, 1); c1 += __shfl_xor_sync(0xffffffffu, c1, 1);
          const uint32_t bw = __ldg(reinterpret_cast<const uint32_t*>(b1 + sp * FC) + (tid >> 1));
          reinterpret_cast<float4*>(smem + SM_WT)[tid >> 1] = make_float4(c0, c1, bflo(bw), bfhi(bw));
        }
        const int row = rt * 128 + warp * 16 + (lane >> 2);
        const float2 st0 = __ldcg(&g_stats[row]), st1 = __ldcg(&g_stats[row + 8]);
        named_bar(1, 256);
        if (tid == 0) {
#pragma unroll 1
          for (int p = 9; p < 12; p++) load_piece(sb, maps, sp, p);
        }
        const float4* csb = reinterpret_cast<const float4*>(smem + SM_WT) + (lane & 3);
#pragma unroll
        for (int j = 0; j < 28; j++) {
          const float4 c = csb[j * 4];
          ha[2 * j] = pack_bf16(gelu2(fmaf(fmaf(-st0.x, c.x, acc[4 * j]), st0.y, c.z)), gelu2(fmaf(fmaf(-st0.x, c.y, acc[4 * j + 1]), st0.y, c.w)));
          ha[2 * j + 1] = pack_bf16(gelu2(fmaf(fmaf(-st1.x, c.x, acc[4 * j + 2]), st1.y, c.z)), gelu2(fmaf(fmaf(-st1.x, c.y, acc[4 * j + 3]), st1.y, c.w)));
        }
      }
      if (tid == 0) TS(4);
      if (wg == 1) named_bar(2, 256);
#pragma unroll 1
      for (int jq = 0; jq < NJOB; jq++) {
        float acc[64];
#pragma unroll
        for (int h = 0; h < 2; h++) {
          const uint32_t o0 = piece_off(4 * jq + 2 * h), o1 = piece_off(4 * jq + 2 * h + 1);
          const uint64_t dW = make_desc(sb + o0, o1 - o0, 1024, 1);
          mbar_wait(bar_full2 + 8 * (2 * jq + h), 0);
          wgmma_fence();
#pragma unroll
          for (int kk = 0; kk < 7; kk++) {
            const int kb = h * 7 + kk;
            wgmma_n128_rs(acc, ha[4 * kb], ha[4 * kb + 1], ha[4 * kb + 2], ha[4 * kb + 3], dW + kk * 128, kb > 0);
          }
          wgmma_commit();
        }
        if (jq == 0 && wg == 0) asm volatile("bar.arrive 2, 256;" ::: "memory");
        wgmma_wait<0>();
        if (jq == 0 && lane == 0) {
          __threadfence_block();
          if (atomicAdd(&relcnt[4], 1u) == 7u) {
            __threadfence_block();
#pragma unroll 1
            for (int p = 12; p < 16; p++) load_piece(sb, maps, sp, p);
          }
        }
        uint4* dstp = g_part + ((((size_t)rt * NJOB + jq) * 8 + warp) * 8 + sp) * 256 + lane;
#pragma unroll
        for (int i = 0; i < 8; i++)
          dstp[i * 32] = make_uint4(pack_bf16(acc[8 * i], acc[8 * i + 1]), pack_bf16(acc[8 * i + 2], acc[8 * i + 3]),
                                    pack_bf16(acc[8 * i + 4], acc[8 * i + 5]), pack_bf16(acc[8 * i + 6], acc[8 * i + 7]));
        __syncwarp();
        if (tid == 0 && jq == 3) TS(8);
      }
}

__global__ void __launch_bounds__(NTHREADS, 1)
k_mega(const __nv_bfloat16* __restrict__ x, const __nv_bfloat16* __restrict__ wr, const __nv_bfloat16* __restrict__ wi,
       const __nv_bfloat16* __restrict__ w1, const __nv_bfloat16* __restrict__ b1, const __nv_bfloat16* __restrict__ b2, __nv_bfloat16* __restrict__ out,
       const __grid_constant__ Maps maps) {
  extern __shared__ __align__(1024) uint8_t smem[];
  const uint32_t sb = smem_u32(smem);
  const int rt = blockIdx.x >> 3, sp = blockIdx.x & 7;
  const int warp = threadIdx.x >> 5, lane = threadIdx.x & 31;
  const int s0 = blockIdx.x * 16;
  if (threadIdx.x == 0) TS(0);
  asm volatile("griddepcontrol.launch_dependents;");
  const uint32_t bar_full1 = sb + SM_BAR;
  const uint32_t bar_full2 = sb + SM_BAR + 64;
  unsigned* relcnt = reinterpret_cast<unsigned*>(smem + SM_BAR + 128);
  const uint32_t bar_stats = sb + SM_BAR + 160;
  const uint32_t bar_p1 = sb + SM_BAR + 168;
  uint8_t* tile = smem + SM_FFT;

  if (threadIdx.x == 0) {
    for (int i = 0; i < 4; i++) mbar_init(bar_full1 + 8 * i, 1);
    for (int i = 0; i < 8; i++) mbar_init(bar_full2 + 8 * i, 2);
    mbar_init(bar_stats, 1); mbar_init(bar_p1, 256);
    for (int i = 0; i < 5; i++) relcnt[i] = 0;
    asm volatile("fence.mbarrier_init.release.cluster;" ::: "memory");
    if (blockIdx.x < 128) {
#pragma unroll 1
      for (int j = 0; j < 4; j++) load_step(sb, maps, rt, sp, j);
    }
  }
  __syncthreads();

  if (warp >= 8) {
    const int t = threadIdx.x & 127;
    const bool extra = blockIdx.x == 128;
    if (!extra) {
      const uint32_t stg = (uint32_t)(SM_WT + (warp - 8) * 2048);
      if (t < 16) {
        const size_t o = (size_t)(s0 + t) * DF_ + 256;
        g_wt[(size_t)256 * S_ + s0 + t] = (uint32_t)__ldg(reinterpret_cast<const unsigned short*>(wr) + o) |
                                          ((uint32_t)__ldg(reinterpret_cast<const unsigned short*>(wi) + o) << 16);
      }
      uint32_t wv[2][16];
      {
        const unsigned short* pr = reinterpret_cast<const unsigned short*>(wr) + (size_t)s0 * DF_ + t;
        const unsigned short* pi = reinterpret_cast<const unsigned short*>(wi) + (size_t)s0 * DF_ + t;
#pragma unroll
        for (int u = 0; u < 32; u++)
          wv[u >> 4][u & 15] = (uint32_t)__ldg(pr + (u & 15) * DF_ + (u >> 4) * 128) | ((uint32_t)__ldg(pi + (u & 15) * DF_ + (u >> 4) * 128) << 16);
      }
#pragma unroll
      for (int rd = 0; rd < 2; rd++) {
        if (rd && lane == 0) asm volatile("cp.async.bulk.wait_group.read 0;" ::: "memory");
        __syncwarp();
#pragma unroll
        for (int c = 0; c < 4; c++)
          *reinterpret_cast<uint4*>(smem + stg + lane * 64 + ((c ^ ((lane >> 1) & 3)) << 4)) =
              make_uint4(wv[rd][4 * c], wv[rd][4 * c + 1], wv[rd][4 * c + 2], wv[rd][4 * c + 3]);
        fence_async();
        __syncwarp();
        if (lane == 0) {
          tma_store_2d(&maps.wt, s0, rd * 128 + (warp - 8) * 32, sb + stg);
          asm volatile("cp.async.bulk.commit_group;" ::: "memory");
        }
      }
      if (lane == 0) { asm volatile("cp.async.bulk.wait_group 0;" ::: "memory"); __threadfence(); }
    }
    named_bar(3, 128);
    if (t == 0) {
      if (!extra) {
        mbar_wait(bar_p1, 0);
        tma_store_2d(&maps.spec, s0, 0, sb + SM_FFT);
        tma_store_commit_wait();
      }
      const unsigned target = grid_arrive(&g_bar[0]);
      grid_wait(&g_bar[0], target);
      mbar_arrive(bar_stats);
    }
    named_bar(3, 128);
    if (t == 0) TS(13);
    {
      float2* buf = reinterpret_cast<float2*>(tile);
      const int k1 = t >> 3, m2 = t & 7;
      const int c0 = extra ? 256 : blockIdx.x * 2, nc = extra ? 1 : 2;
      float2 vn[16];
      uint32_t wn[16];
#pragma unroll 1
      for (int c = -1; c < nc; c++) {
        uint32_t wq[16];
        if (c >= 0) {
#pragma unroll
          for (int i = 0; i < 16; i++) { buf[128 * i + t] = vn[i]; wq[i] = wn[i]; }
        }
        if (c + 1 < nc) {
#pragma unroll
          for (int i = 0; i < 16; i++) {
            vn[i] = __ldcg(g_spec + (size_t)(c0 + c + 1) * S_ + 128 * i + t);
            wn[i] = __ldcg(g_wt + (size_t)(c0 + c + 1) * S_ + 128 * i + t);
          }
        }
        if (c < 0) continue;
#pragma unroll 1
        for (int it = 0; it < 2; it++) {
#pragma unroll 1
          for (int p = 0; p < 2; p++) {
            const float2* in = buf + (p ? k1 * 136 + m2 : t);
            const int is = p ? 8 : 128;
            float2 v[16];
#pragma unroll
            for (int i = 0; i < 16; i++) v[i] = in[i * is];
            dft16<-1>(v);
            twiddle16(v, p ? 16 * m2 : t);
            named_bar(3, 128);
            float2* o = buf + (p ? k1 * 9 + m2 : t);
            const int os = p ? 144 : 136;
#pragma unroll
            for (int kk = 0; kk < 16; kk++) o[kk * os] = v[O16(kk)];
            named_bar(3, 128);
          }
          float2 e[2][8];
#pragma unroll
          for (int m = 0; m < 8; m++) { e[0][m] = buf[t * 9 + m]; e[1][m] = buf[(t + 128) * 9 + m]; }
          dft8<-1>(e[0]);
          dft8<-1>(e[1]);
          named_bar(3, 128);
          if (it == 0) {
            constexpr float SC = 1.0f / (2048.0f * 512.0f);
#pragma unroll
            for (int i = 0; i < 16; i++)
              buf[128 * i + t] = cconj(cmul(e[i & 1][O8(i >> 1)], make_float2(bflo(wq[i]) * SC, bfhi(wq[i]) * SC)));
          } else {
            float2* col = g_spec + (size_t)(c0 + c) * S_ + t;
#pragma unroll
            for (int i = 0; i < 16; i++) col[128 * i] = cconj(e[i & 1][O8(i >> 1)]);
          }
        }
      }
    }
    if (t == 0) TS(14);
  } else {
    if (blockIdx.x == 128) return;
    const int tid = threadIdx.x;
    const int r = tid & 15, q = tid >> 4;
    {
        uint32_t w[16];
        const uint32_t* xw = reinterpret_cast<const uint32_t*>(x + (size_t)(s0 + q) * D_);
#pragma unroll
        for (int n1 = 0; n1 < 16; n1++) w[n1] = __ldg(xw + 16 * n1 + r);
        if ((tid & 127) < 112) {
          const uint32_t* pw = reinterpret_cast<const uint32_t*>(w1 + (size_t)(rt * 32 + (tid >> 7) * 16) * F_ + sp * FC) + (tid & 127);
          float c0 = 0.f, c1 = 0.f;
#pragma unroll
          for (int k = 0; k < 16; k++) { const uint32_t ww = __ldg(pw + k * (F_ / 2)); c0 += bflo(ww); c1 += bfhi(ww); }
          g_cs[(sp * 32 + rt * 2 + (tid >> 7)) * 112 + (tid & 127)] = make_float2(c0, c1);
        }
        float sum = 0.f;
#pragma unroll
        for (int n1 = 0; n1 < 16; n1++) sum += bflo(w[n1]) + bfhi(w[n1]);
#pragma unroll
        for (int o = 1; o < 16; o <<= 1) sum += __shfl_xor_sync(0xffffffffu, sum, o);
        const float mean = sum * (1.0f / D_);
        float sq = 0.f;
#pragma unroll
        for (int n1 = 0; n1 < 16; n1++) {
          float a = bflo(w[n1]) - mean, c = bfhi(w[n1]) - mean;
          sq += a * a + c * c;
        }
#pragma unroll
        for (int o = 1; o < 16; o <<= 1) sq += __shfl_xor_sync(0xffffffffu, sq, o);
        const uint32_t nm2 = pack_bf16(-mean, -mean);
        float sd, rs;
        asm("sqrt.approx.f32 %0, %1;" : "=f"(sd) : "f"(bf16r(bf16r(sq * (1.0f / D_)) + 1e-5f)));
        asm("rcp.approx.f32 %0, %1;" : "=f"(rs) : "f"(bf16r(sd)));
        if (r == 0) g_stats[s0 + q] = make_float2(-bflo(nm2), rs);
#pragma unroll
        for (int n1 = 0; n1 < 16; n1++) {
          const uint32_t d = hadd2_bf16(w[n1], nm2);
          const uint32_t xn = pack_bf16(bflo(d) * rs, bfhi(d) * rs);
          *tile_at(tile, 16 * n1 + r, q) = make_float2(bflo(xn), bfhi(xn));
        }
      }
      named_bar(1, 256);
      {
        uint8_t* pa = reinterpret_cast<uint8_t*>(tile_at(tile, q, r));
        const uint8_t* pb = tile + q * 2048 + (r & 1) * 8;
        float2 v[16];
#pragma unroll
        for (int i = 0; i < 16; i++) v[i] = *reinterpret_cast<const float2*>(pa + i * 2048);
        dft16<-1>(v);
        twiddle16(v, 8 * q);
#pragma unroll
        for (int i = 0; i < 16; i++) *reinterpret_cast<float2*>(pa + i * 2048) = v[O16(i)];
        named_bar(1, 256);
#pragma unroll
        for (int i = 0; i < 16; i++) v[i] = *reinterpret_cast<const float2*>(pb + i * 128 + ((((r >> 1) ^ i) & 7) << 4));
        dft16<-1>(v);
        named_bar(1, 256);
#pragma unroll
        for (int i = 0; i < 16; i++) *reinterpret_cast<float2*>(pa + i * 2048) = v[O16(i)];
        named_bar(1, 256);
      }
    {
        float2 tw = twcs<512>(q);
#pragma unroll
        for (int i = 0; i < 8; i++) {
          const int j = q + 16 * i;
          float2* pa = tile_at(tile, j, r);
          float2* pb = tile_at(tile, j == 0 ? 128 : 256 - j, r);
          const float2 A = *pa, B = *pb;
          const float2 P = make_float2(0.5f * (A.x + B.x), 0.5f * (A.y - B.y)), M = make_float2(0.5f * (A.x - B.x), 0.5f * (A.y + B.y));
          const float2 T = make_float2(M.x * tw.x + M.y * tw.y, M.y * tw.x - M.x * tw.y);
          tw = cmul(tw, make_float2(0.98078528040323044f, 0.19509032201612825f));
          if (j == 0) g_spec[(size_t)256 * S_ + s0 + r] = make_float2(A.x - A.y, 0.f);
          *pa = j ? make_float2(P.x + T.y, P.y - T.x) : make_float2(A.x + A.y, 0.f);
          *pb = j ? make_float2(P.x - T.y, -(P.y + T.x)) : cconj(B);
        }
    }
    fence_async();
    mbar_arrive(bar_p1);
    gemm_part(smem, maps, b1, rt, sp);
  }
}

__global__ void __launch_bounds__(256, 1)
k_tail(const __nv_bfloat16* __restrict__ x, const __nv_bfloat16* __restrict__ b2, __nv_bfloat16* __restrict__ out,
       const __grid_constant__ CUtensorMap map_spec) {
  extern __shared__ __align__(1024) uint8_t tsm[];
  uint8_t* tile = tsm;
  __shared__ __align__(8) uint64_t bar, barg[NJOB];
  const int rt = blockIdx.x >> 3, sp = blockIdx.x & 7, s0 = blockIdx.x * 16;
  const int tid = threadIdx.x, warp = tid >> 5, lane = tid & 31;
  const int r = tid & 15, q = tid >> 4, g = lane >> 2;
  if (tid == 0) {
    mbar_init(smem_u32(&bar), 1);
    for (int i = 0; i < NJOB; i++) mbar_init(smem_u32(&barg[i]), 1);
    asm volatile("fence.mbarrier_init.release.cluster;" ::: "memory");
  }
  uint32_t bw[NJOB][2], xw[NJOB][4];
#pragma unroll
  for (int jq = 0; jq < NJOB; jq++) {
    const int cw = jq * 64 + 8 * warp + (lane & 3);
#pragma unroll
    for (int c = 0; c < 4; c++) {
      if (!(c & 1)) bw[jq][c >> 1] = __ldg(reinterpret_cast<const uint32_t*>(b2) + cw + 4 * (c >> 1));
      xw[jq][c] = __ldg(reinterpret_cast<const uint32_t*>(x) + (size_t)(s0 + g + 8 * (c & 1)) * 256 + cw + 4 * (c >> 1));
    }
  }
  if (tid == 0) TS(28);
  asm volatile("griddepcontrol.wait;" ::: "memory");
  if (tid == 0) TS(29);
  if (tid == 0) {
    mbar_expect_tx(smem_u32(&bar), 32768);
    tma_load_2d(smem_u32(tile), &map_spec, s0, 0, smem_u32(&bar));
#pragma unroll 1
    for (int jq = 0; jq < NJOB; jq++) {
      mbar_expect_tx(smem_u32(&barg[jq]), 32768);
      asm volatile("cp.async.bulk.shared::cluster.global.mbarrier::complete_tx::bytes [%0], [%1], %2, [%3];"
                   ::"r"(smem_u32(tsm) + 32768 + jq * 32768), "l"(g_part + (((size_t)rt * NJOB + jq) * 8 + sp) * 8 * 256), "r"(32768), "r"(smem_u32(&barg[jq])) : "memory");
    }
  }
  const float y256 = __ldcg(&g_spec[(size_t)256 * S_ + s0 + r]).x;
  __syncthreads();
  mbar_wait(smem_u32(&bar), 0);
  if (tid == 0) TS(27);
  {
    float2 tw = twcs<512>(q);
#pragma unroll
    for (int i = 0; i < 8; i++) {
      const int j = q + 16 * i;
      float2* pa = tile_at(tile, j, r);
      float2* pb = tile_at(tile, j == 0 ? 128 : 256 - j, r);
      const float2 A = *pa, B = *pb;
      const float2 P = make_float2(A.x + B.x, A.y - B.y), M = make_float2(A.x - B.x, A.y + B.y);
      const float2 T = make_float2(M.x * tw.x - M.y * tw.y, M.y * tw.x + M.x * tw.y);
      tw = cmul(tw, make_float2(0.98078528040323044f, 0.19509032201612825f));
      *pa = j ? make_float2(P.x - T.y, -(P.y + T.x)) : make_float2(A.x + y256, y256 - A.x);
      *pb = j ? make_float2(P.x + T.y, P.y - T.x) : make_float2(2.f * B.x, 2.f * B.y);
    }
  }
  __syncthreads();
  {
    uint8_t* pa = reinterpret_cast<uint8_t*>(tile_at(tile, q, r));
    const uint8_t* pb = tile + q * 2048 + (r & 1) * 8;
    float2 w[16];
#pragma unroll
    for (int i = 0; i < 16; i++) w[i] = *reinterpret_cast<const float2*>(pa + i * 2048);
    dft16<-1>(w);
    twiddle16(w, 8 * q);
#pragma unroll
    for (int i = 0; i < 16; i++) *reinterpret_cast<float2*>(pa + i * 2048) = w[O16(i)];
    __syncthreads();
#pragma unroll
    for (int i = 0; i < 16; i++) w[i] = *reinterpret_cast<const float2*>(pb + i * 128 + ((((r >> 1) ^ i) & 7) << 4));
    dft16<-1>(w);
    __syncthreads();
#pragma unroll
    for (int i = 0; i < 16; i++) reinterpret_cast<uint32_t*>(tile)[r * SPITCH + q + 16 * i] = pack_bf16(w[O16(i)].x, -w[O16(i)].y);
  }
  __syncthreads();
  const uint32_t* stile = reinterpret_cast<const uint32_t*>(tile);
  if (tid == 0) TS(30);
#pragma unroll
  for (int jq = 0; jq < NJOB; jq++) {
    const int cw = jq * 64 + 8 * warp + (lane & 3);
    mbar_wait(smem_u32(&barg[jq]), 0);
    const uint4* src = reinterpret_cast<const uint4*>(tsm + 32768 + jq * 32768) + tid;
    float o[8];
#pragma unroll
    for (int c = 0; c < 8; c++) o[c] = 0.f;
#pragma unroll
    for (int s = 0; s < 8; s++) {
      const uint4 v = src[s * 256];
      o[0] += bflo(v.x); o[1] += bfhi(v.x); o[2] += bflo(v.y); o[3] += bfhi(v.y);
      o[4] += bflo(v.z); o[5] += bfhi(v.z); o[6] += bflo(v.w); o[7] += bfhi(v.w);
    }
#pragma unroll
    for (int c = 0; c < 4; c++) {
      const int row = g + 8 * (c & 1), w = cw + 4 * (c >> 1);
      const uint32_t sw = stile[row * SPITCH + w];
      const uint32_t p = hadd2_bf16(pack_bf16(0.5f * o[2 * c], 0.5f * o[2 * c + 1]), bw[jq][c >> 1]);
      const float oa = bflo(p), ob = bfhi(p);
      const uint32_t gg = pack_bf16(__fdividef(oa, 1.0f + __expf(-oa)), __fdividef(ob, 1.0f + __expf(-ob)));
      const uint32_t sg = pack_bf16(bflo(sw) * bflo(gg), bfhi(sw) * bfhi(gg));
      reinterpret_cast<uint32_t*>(out)[(size_t)(s0 + row) * 256 + w] = hadd2_bf16(xw[jq][c], sg);
    }
  }
  if (tid == 0) TS(31);
}

typedef CUresult (*EncodeFn)(CUtensorMap*, CUtensorMapDataType, cuuint32_t, void*, const cuuint64_t*, const cuuint64_t*,
                             const cuuint32_t*, const cuuint32_t*, CUtensorMapInterleave, CUtensorMapSwizzle,
                             CUtensorMapL2promotion, CUtensorMapFloatOOBfill);

}

extern "C" void kernel_launch(void* const* d_in, const int* in_sizes, int n_in, void* d_out, int out_size) {
  const __nv_bfloat16* x = (const __nv_bfloat16*)d_in[0];
  const __nv_bfloat16* wr = (const __nv_bfloat16*)d_in[1];
  const __nv_bfloat16* wi = (const __nv_bfloat16*)d_in[2];
  const __nv_bfloat16* w1 = (const __nv_bfloat16*)d_in[4];
  const __nv_bfloat16* b1 = (const __nv_bfloat16*)d_in[5];
  const __nv_bfloat16* w2 = (const __nv_bfloat16*)d_in[6];
  const __nv_bfloat16* b2 = (const __nv_bfloat16*)d_in[7];
  __nv_bfloat16* out = (__nv_bfloat16*)d_out;

  static EncodeFn enc = nullptr;
  static void* p_spec = nullptr;
  static void* p_wt = nullptr;
  if (!enc) {
    void* fn = nullptr;
    cudaDriverEntryPointQueryResult qr;
    cudaGetDriverEntryPoint("cuTensorMapEncodeTiled", &fn, cudaEnableDefault, &qr);
    enc = (EncodeFn)fn;
    cudaFuncSetAttribute(k_mega, cudaFuncAttributeMaxDynamicSharedMemorySize, SM_TOTAL);
    cudaFuncSetAttribute(k_tail, cudaFuncAttributeMaxDynamicSharedMemorySize, 5 * 32768);
    cudaGetSymbolAddress(&p_spec, g_spec);
    cudaGetSymbolAddress(&p_wt, g_wt);
  }
  Maps m;
  const cuuint32_t es[3] = {1, 1, 1};
  {
    cuuint64_t dims[2] = {(cuuint64_t)D_, (cuuint64_t)S_};
    cuuint64_t strides[1] = {(cuuint64_t)D_ * 2};
    cuuint32_t box[2] = {64, 128};
    enc(&m.x, CU_TENSOR_MAP_DATA_TYPE_BFLOAT16, 2, (void*)x, dims, strides, box, es, CU_TENSOR_MAP_INTERLEAVE_NONE,
        CU_TENSOR_MAP_SWIZZLE_128B, CU_TENSOR_MAP_L2_PROMOTION_L2_128B, CU_TENSOR_MAP_FLOAT_OOB_FILL_NONE);
  }
  {
    cuuint64_t dims[3] = {32, 512, 56};
    cuuint64_t strides[2] = {(cuuint64_t)F_ * 2, 64};
    cuuint32_t box[3] = {32, 32, 7};
    enc(&m.w1, CU_TENSOR_MAP_DATA_TYPE_BFLOAT16, 3, (void*)w1, dims, strides, box, es, CU_TENSOR_MAP_INTERLEAVE_NONE,
        CU_TENSOR_MAP_SWIZZLE_64B, CU_TENSOR_MAP_L2_PROMOTION_L2_128B, CU_TENSOR_MAP_FLOAT_OOB_FILL_NONE);
  }
  {
    cuuint64_t dims[2] = {(cuuint64_t)D_, (cuuint64_t)F_};
    cuuint64_t strides[1] = {(cuuint64_t)D_ * 2};
    cuuint32_t box[2] = {64, 112};
    enc(&m.w2, CU_TENSOR_MAP_DATA_TYPE_BFLOAT16, 2, (void*)w2, dims, strides, box, es, CU_TENSOR_MAP_INTERLEAVE_NONE,
        CU_TENSOR_MAP_SWIZZLE_128B, CU_TENSOR_MAP_L2_PROMOTION_L2_128B, CU_TENSOR_MAP_FLOAT_OOB_FILL_NONE);
  }
  {
    cuuint64_t dims[2] = {(cuuint64_t)S_, 256};
    cuuint64_t strides[1] = {(cuuint64_t)S_ * 8};
    cuuint32_t box[2] = {16, 256};
    enc(&m.spec, CU_TENSOR_MAP_DATA_TYPE_FLOAT64, 2, p_spec, dims, strides, box, es, CU_TENSOR_MAP_INTERLEAVE_NONE,
        CU_TENSOR_MAP_SWIZZLE_128B, CU_TENSOR_MAP_L2_PROMOTION_NONE, CU_TENSOR_MAP_FLOAT_OOB_FILL_NONE);
  }
  {
    cuuint64_t dims[2] = {(cuuint64_t)S_, 257};
    cuuint64_t strides[1] = {(cuuint64_t)S_ * 4};
    cuuint32_t box[2] = {16, 32};
    enc(&m.wt, CU_TENSOR_MAP_DATA_TYPE_UINT32, 2, p_wt, dims, strides, box, es, CU_TENSOR_MAP_INTERLEAVE_NONE,
        CU_TENSOR_MAP_SWIZZLE_64B, CU_TENSOR_MAP_L2_PROMOTION_NONE, CU_TENSOR_MAP_FLOAT_OOB_FILL_NONE);
  }
  k_mega<<<129, NTHREADS, SM_TOTAL>>>(x, wr, wi, w1, b1, b2, out, m);
  cudaLaunchConfig_t cfg = {};
  cfg.gridDim = dim3(128); cfg.blockDim = dim3(256); cfg.dynamicSmemBytes = 5 * 32768; cfg.stream = cudaStreamPerThread;
  cudaLaunchAttribute at[1];
  at[0].id = cudaLaunchAttributeProgrammaticStreamSerialization;
  at[0].val.programmaticStreamSerializationAllowed = 1;
  cfg.attrs = at; cfg.numAttrs = 1;
  cudaLaunchKernelEx(&cfg, k_tail, x, b2, out, m.spec);
}
```
